```python
import torch

def _softmax(x, axis=-1):
    return torch.softmax(x, dim=axis)

def _gelu(x):
    return torch.nn.functional.gelu(x, approximate='tanh')

def _silu(x):
    return torch.nn.functional.silu(x)

def _sigmoid(x):
    return torch.sigmoid(x)

def _layernorm(x, axis=-1, eps=1e-05):
    m = x.mean(dim=axis, keepdim=True)
    v = x.var(dim=axis, keepdim=True, unbiased=False)
    return (x - m) / torch.sqrt(v + eps)

def _scatter_add(tgt, idx, src, axis=0):
    return tgt.clone().index_add_(axis, idx, src)

def _segment_sum(src, seg, n):
    out = torch.zeros((n,) + src.shape[1:], dtype=src.dtype)
    return out.index_add_(0, seg, src)

def _pad(x, pw):
    flat = tuple((v for pair in reversed(pw) for v in pair))
    return torch.nn.functional.pad(x, flat)
kernel_name = 'standalone__tree_speculative_verify_tree_attention_over_candidate_token_tree__sampling'

def setup_inputs():

    _w = lambda a: (lambda t: t.to(torch.bfloat16) if t.is_floating_point() else t)(torch.as_tensor(a))
    B, Hq, Hkv, T, C, D = (32, 32, 16, 8, 2048, 128)
    tree_mask = torch.zeros((B, T, T), dtype=float)
    for b in range(B):
        parent = torch.zeros(T, dtype=torch.int64)
        for i in range(1, T):
            parent[i] = int(torch.randint(0, i, (1,)).item())
        for i in range(T):
            j = i
            tree_mask[b, i, j] = 1.0
            while j > 0:
                j = parent[j]
                tree_mask[b, i, j] = 1.0
    return {'q': _w((lambda *s: torch.randn(*s, dtype=torch.bfloat16) * 0.8)(B, Hq, T, D)), 'k_cache': _w((lambda *s: torch.randn(*s, dtype=torch.bfloat16) * 0.8)(B, Hkv, C, D)), 'v_cache': _w((lambda *s: torch.randn(*s, dtype=torch.bfloat16) * 0.05)(B, Hkv, C, D)), 'k_tree': _w((lambda *s: torch.randn(*s, dtype=torch.bfloat16) * 0.8)(B, Hkv, T, D)), 'v_tree': _w((lambda *s: torch.randn(*s, dtype=torch.bfloat16) * 0.05)(B, Hkv, T, D)), 'tree_mask': _w(tree_mask)}

def reference(q, k_cache, v_cache, k_tree, v_tree, tree_mask):
    B, Hq, T, D = q.shape
    Hkv, C = (k_cache.shape[1], k_cache.shape[2])
    rep = Hq // Hkv
    kc = (lambda x, n, axis: torch.repeat_interleave(x, n, dim=axis))(k_cache, rep, axis=1)
    vc = (lambda x, n, axis: torch.repeat_interleave(x, n, dim=axis))(v_cache, rep, axis=1)
    kt = (lambda x, n, axis: torch.repeat_interleave(x, n, dim=axis))(k_tree, rep, axis=1)
    vt = (lambda x, n, axis: torch.repeat_interleave(x, n, dim=axis))(v_tree, rep, axis=1)
    k = torch.concatenate([kc, kt], axis=2)
    v = torch.concatenate([vc, vt], axis=2)
    scale = D ** (-0.5)
    scores = torch.einsum('bhqd,bhkd->bhqk', q, k) * scale
    ctx_mask = torch.ones((B, 1, T, C), dtype=scores.dtype)
    tm = tree_mask[:, None, :, :].clone()
    full_mask = torch.concatenate([ctx_mask, tm], axis=-1)
    scores = scores + (1.0 - full_mask) * -1000000000.0
    p = _softmax(scores, axis=-1)
    return torch.einsum('bhqk,bhkd->bhqd', p, v)
```

```cpp
#include <cuda_runtime.h>
#include <cuda_bf16.h>
#include <cuda.h>
#include <stdint.h>

#define CFG_NS 8
#define CFG_INFLIGHT 4
#define CFG_RUN 4
#define CFG_HINT 1

namespace {

constexpr int kB = 32, kHkv = 16, kT = 8, kC = 2048, kD = 128;
constexpr int kPairs = kB * kHkv;
constexpr int kGrid = 128;
constexpr int kPairsPerCta = kPairs / kGrid;
constexpr int kTileKeys = 64;
constexpr int kTileBytes = kTileKeys * kD * 2;
constexpr int kRun = CFG_RUN;
constexpr int kRunsPerPair = kC / (kTileKeys * kRun);
constexpr int kTilesPerPair = 2 * kC / kTileKeys;
constexpr int kNS = CFG_NS;
constexpr int kInflight = CFG_INFLIGHT;
constexpr int kCW = 4;
constexpr int kThreads = (kCW + 1) * 32;

constexpr int kAuxQ = 0, kAuxKt = 4096, kAuxVt = 6144, kAuxMask = 8192, kAuxBytes = 8320;
constexpr int kORow = 136;

constexpr int kSmRing = 0;
constexpr int kSmAux = kSmRing + kNS * kTileBytes;
constexpr int kSmO = kSmAux + kPairsPerCta * kAuxBytes;
constexpr int kSmML = kSmO + kCW * 16 * kORow * 4;
constexpr int kSmBar = kSmML + kCW * 16 * 2 * 4;
constexpr int kSmTotal = kSmBar + (2 * kNS + kPairsPerCta) * 8;
constexpr int kSmemBytes = kSmTotal + 1024;

__device__ __forceinline__ uint32_t smem_u32(const void* p) {
    return (uint32_t)__cvta_generic_to_shared(p);
}
__device__ __forceinline__ void mbar_init(uint32_t bar, int cnt) {
    asm volatile("mbarrier.init.shared::cta.b64 [%0], %1;" ::"r"(bar), "r"(cnt) : "memory");
}
__device__ __forceinline__ void mbar_expect_tx(uint32_t bar, uint32_t bytes) {
    asm volatile("mbarrier.arrive.expect_tx.shared::cta.b64 _, [%0], %1;" ::"r"(bar), "r"(bytes) : "memory");
}
__device__ __forceinline__ void mbar_arrive(uint32_t bar) {
    asm volatile("mbarrier.arrive.shared::cta.b64 _, [%0];" ::"r"(bar) : "memory");
}
__device__ __forceinline__ bool mbar_try(uint32_t bar, uint32_t parity) {
    uint32_t ok;
    asm volatile(
        "{\n.reg .pred p;\n"
        "mbarrier.try_wait.parity.shared::cta.b64 p, [%1], %2;\n"
        "selp.u32 %0, 1, 0, p;\n}"
        : "=r"(ok) : "r"(bar), "r"(parity) : "memory");
    return ok != 0;
}
__device__ __forceinline__ void mbar_wait(uint32_t bar, uint32_t parity) {
    for (uint32_t it = 0; !mbar_try(bar, parity); ++it) {
        if (it > (1u << 24)) __trap();
    }
}
__device__ __forceinline__ void bulk_load(uint32_t dst, const void* src, uint32_t bytes, uint32_t bar) {
    asm volatile(
        "cp.async.bulk.shared::cluster.global.mbarrier::complete_tx::bytes [%0], [%1], %2, [%3];"
        ::"r"(dst), "l"(src), "r"(bytes), "r"(bar) : "memory");
}
__device__ __forceinline__ void tma_tile(uint32_t dst, const CUtensorMap* tm, int key, uint32_t bar, uint64_t pol) {
    asm volatile(
        "cp.async.bulk.tensor.3d.shared::cluster.global.mbarrier::complete_tx::bytes.L2::cache_hint "
        "[%0], [%1, {%3, %4, %5}], [%2], %6;"
        ::"r"(dst), "l"(tm), "r"(bar), "r"(0), "r"(key), "r"(0), "l"(pol) : "memory");
}
__device__ __forceinline__ void ldsm4(uint32_t& r0, uint32_t& r1, uint32_t& r2, uint32_t& r3, uint32_t addr) {
    asm volatile("ldmatrix.sync.aligned.m8n8.x4.shared.b16 {%0,%1,%2,%3}, [%4];"
                 : "=r"(r0), "=r"(r1), "=r"(r2), "=r"(r3) : "r"(addr) : "memory");
}
__device__ __forceinline__ void ldsm4t(uint32_t& r0, uint32_t& r1, uint32_t& r2, uint32_t& r3, uint32_t addr) {
    asm volatile("ldmatrix.sync.aligned.m8n8.x4.trans.shared.b16 {%0,%1,%2,%3}, [%4];"
                 : "=r"(r0), "=r"(r1), "=r"(r2), "=r"(r3) : "r"(addr) : "memory");
}
__device__ __forceinline__ void mma16816(float (&c)[4], uint32_t a0, uint32_t a1, uint32_t a2, uint32_t a3,
                                         uint32_t b0, uint32_t b1) {
    asm("mma.sync.aligned.m16n8k16.row.col.f32.bf16.bf16.f32 {%0,%1,%2,%3}, {%4,%5,%6,%7}, {%8,%9}, {%0,%1,%2,%3};"
        : "+f"(c[0]), "+f"(c[1]), "+f"(c[2]), "+f"(c[3])
        : "r"(a0), "r"(a1), "r"(a2), "r"(a3), "r"(b0), "r"(b1));
}
__device__ __forceinline__ float ex2(float x) {
    float y;
    asm("ex2.approx.ftz.f32 %0, %1;" : "=f"(y) : "f"(x));
    return y;
}
__device__ __forceinline__ uint32_t pack_bf16(float lo, float hi) {
    uint32_t r;
    asm("cvt.rn.bf16x2.f32 %0, %1, %2;" : "=r"(r) : "f"(hi), "f"(lo));
    return r;
}
__device__ __forceinline__ float quad_max(float v) {
    v = fmaxf(v, __shfl_xor_sync(0xffffffffu, v, 1));
    v = fmaxf(v, __shfl_xor_sync(0xffffffffu, v, 2));
    return v;
}
__device__ __forceinline__ float quad_sum(float v) {
    v += __shfl_xor_sync(0xffffffffu, v, 1);
    v += __shfl_xor_sync(0xffffffffu, v, 2);
    return v;
}

__global__ void __launch_bounds__(kThreads, 1)
tree_attn_kernel(const __grid_constant__ CUtensorMap tmK, const __grid_constant__ CUtensorMap tmV,
                 const __nv_bfloat16* __restrict__ q, const __nv_bfloat16* __restrict__ k_tree,
                 const __nv_bfloat16* __restrict__ v_tree, const __nv_bfloat16* __restrict__ mask,
                 __nv_bfloat16* __restrict__ out) {
    extern __shared__ unsigned char smem_raw[];
    const uint32_t sraw = smem_u32(smem_raw);
    const uint32_t sb = (sraw + 1023u) & ~1023u;
    unsigned char* sgen = smem_raw + (sb - sraw);

    const uint32_t bar_full = sb + kSmBar;
    const uint32_t bar_empty = bar_full + kNS * 8;
    const uint32_t bar_aux = bar_empty + kNS * 8;

    const int warp = threadIdx.x >> 5;
    const int lane = threadIdx.x & 31;

    if (warp == kCW) {
        uint64_t pol = 0;
        auto issue = [&](int i) {
            const int u = i / kTilesPerPair;
            const int r = i % kTilesPerPair;
            const int pair = blockIdx.x + u * kGrid;
            if (r == 0) {
                const uint32_t ab = bar_aux + u * 8;
                const uint32_t dst = sb + kSmAux + u * kAuxBytes;
                mbar_expect_tx(ab, 4096 + 2048 + 2048 + 128);
                bulk_load(dst + kAuxQ, q + (size_t)pair * 16 * kD, 4096, ab);
                bulk_load(dst + kAuxKt, k_tree + (size_t)pair * kT * kD, 2048, ab);
                bulk_load(dst + kAuxVt, v_tree + (size_t)pair * kT * kD, 2048, ab);
                bulk_load(dst + kAuxMask, mask + (size_t)(pair / kHkv) * kT * kT, 128, ab);
            }
            const int run = r / (2 * kRun);
            const int w = r % (2 * kRun);
            const int is_v = w / kRun;
            const int key = pair * kC + (run * kRun + (w % kRun)) * kTileKeys;
            const int slot = i % kNS;
            const uint32_t fb = bar_full + slot * 8;
            mbar_expect_tx(fb, kTileBytes);
            tma_tile(sb + kSmRing + slot * kTileBytes, is_v ? &tmV : &tmK, key, fb, pol);
        };
        if (lane == 0) {
            for (int s = 0; s < kNS; ++s) {
                mbar_init(bar_full + s * 8, 1);
                mbar_init(bar_empty + s * 8, kCW);
            }
            for (int u = 0; u < kPairsPerCta; ++u) mbar_init(bar_aux + u * 8, 1);
            asm volatile("fence.mbarrier_init.release.cluster;" ::: "memory");
            asm volatile("fence.proxy.async.shared::cta;" ::: "memory");
            asm volatile("createpolicy.fractional.L2::evict_first.b64 %0, 1.0;" : "=l"(pol));
            for (int i = 0; i < kInflight; ++i) issue(i);
        }
        __syncthreads();
        if (lane == 0) {
            constexpr int kTotal = kPairsPerCta * kTilesPerPair;
            for (int i = kInflight; i < kTotal; ++i) {
                if (i >= kNS) mbar_wait(bar_empty + (i % kNS) * 8, ((i / kNS) - 1) & 1);
                const int j = i - kInflight;
                mbar_wait(bar_full + (j % kNS) * 8, (j / kNS) & 1);
                issue(i);
            }
        }
    } else {
        __syncthreads();
        const int g = lane >> 2;
        const int tq = lane & 3;
        const int mi = lane >> 3;
        const int lr = lane & 7;
        const float c = 0.08838834764831845f * 1.4426950408889634f;

        const uint32_t k_row = (uint32_t)(16 * warp + 8 * (mi >> 1) + lr) * 128u;
        const uint32_t k_x = (uint32_t)(((mi & 1) ^ lr) << 4);
        const uint32_t v_row = (uint32_t)(16 * warp + 8 * (mi & 1) + lr) * 128u;
        const uint32_t v_x = (uint32_t)(((mi >> 1) ^ lr) << 4);

        int slot = 0;
        uint32_t phase = 0;

        for (int u = 0; u < kPairsPerCta; ++u) {
            const int pair = blockIdx.x + u * kGrid;
            const uint32_t aux = sb + kSmAux + u * kAuxBytes;
            mbar_wait(bar_aux + u * 8, 0);

            uint32_t qf[8][4];
            {
                const uint32_t qa = aux + kAuxQ + (uint32_t)(lr + 8 * (mi & 1)) * 256u + (uint32_t)(mi >> 1) * 16u;
#pragma unroll
                for (int s = 0; s < 8; ++s) ldsm4(qf[s][0], qf[s][1], qf[s][2], qf[s][3], qa + s * 32);
            }

            float o[16][4];
#pragma unroll
            for (int n = 0; n < 16; ++n) { o[n][0] = 0.f; o[n][1] = 0.f; o[n][2] = 0.f; o[n][3] = 0.f; }
            float m0 = -INFINITY, m1 = -INFINITY, l0 = 0.f, l1 = 0.f;

            if (warp == (u & (kCW - 1))) {
                float st[4] = {0.f, 0.f, 0.f, 0.f};
                const uint32_t ka = aux + kAuxKt + (uint32_t)lr * 256u + (uint32_t)mi * 16u;
#pragma unroll
                for (int s2 = 0; s2 < 4; ++s2) {
                    uint32_t b0, b1, b2, b3;
                    ldsm4(b0, b1, b2, b3, ka + s2 * 64);
                    mma16816(st, qf[2 * s2][0], qf[2 * s2][1], qf[2 * s2][2], qf[2 * s2][3], b0, b1);
                    mma16816(st, qf[2 * s2 + 1][0], qf[2 * s2 + 1][1], qf[2 * s2 + 1][2], qf[2 * s2 + 1][3], b2, b3);
                }
                const __nv_bfloat162 mk =
                    *reinterpret_cast<const __nv_bfloat162*>(sgen + kSmAux + u * kAuxBytes + kAuxMask + (g * kT + 2 * tq) * 2);
                const float bias0 = (1.0f - __low2float(mk)) * (-1.0e9f * 1.4426950408889634f);
                const float bias1 = (1.0f - __high2float(mk)) * (-1.0e9f * 1.4426950408889634f);
                const float t0 = fmaf(st[0], c, bias0), t1 = fmaf(st[1], c, bias1);
                const float t2 = fmaf(st[2], c, bias0), t3 = fmaf(st[3], c, bias1);
                m0 = quad_max(fmaxf(t0, t1));
                m1 = quad_max(fmaxf(t2, t3));
                const float p0 = ex2(t0 - m0), p1 = ex2(t1 - m0), p2 = ex2(t2 - m1), p3 = ex2(t3 - m1);
                l0 = p0 + p1;
                l1 = p2 + p3;
                const uint32_t a0 = pack_bf16(p0, p1), a1 = pack_bf16(p2, p3);
                const uint32_t va = aux + kAuxVt + (uint32_t)lr * 256u + (uint32_t)mi * 16u;
#pragma unroll
                for (int n4 = 0; n4 < 4; ++n4) {
                    uint32_t b0, b1, b2, b3;
                    ldsm4t(b0, b1, b2, b3, va + n4 * 64);
                    mma16816(o[4 * n4 + 0], a0, a1, 0u, 0u, b0, 0u);
                    mma16816(o[4 * n4 + 1], a0, a1, 0u, 0u, b1, 0u);
                    mma16816(o[4 * n4 + 2], a0, a1, 0u, 0u, b2, 0u);
                    mma16816(o[4 * n4 + 3], a0, a1, 0u, 0u, b3, 0u);
                }
            }

            for (int run = 0; run < kRunsPerPair; ++run) {
                float s[kRun][2][4];
#pragma unroll
                for (int t = 0; t < kRun; ++t) {
                    const uint32_t base = sb + kSmRing + slot * kTileBytes + k_row;
                    mbar_wait(bar_full + slot * 8, phase);
#pragma unroll
                    for (int e = 0; e < 4; ++e) { s[t][0][e] = 0.f; s[t][1][e] = 0.f; }
#pragma unroll
                    for (int ks = 0; ks < 8; ++ks) {
                        uint32_t b0, b1, b2, b3;
                        ldsm4(b0, b1, b2, b3, base + (ks >> 2) * 8192 + (k_x ^ ((ks & 3) << 5)));
                        mma16816(s[t][0], qf[ks][0], qf[ks][1], qf[ks][2], qf[ks][3], b0, b1);
                        mma16816(s[t][1], qf[ks][0], qf[ks][1], qf[ks][2], qf[ks][3], b2, b3);
                    }
                    __syncwarp();
                    if (lane == 0) mbar_arrive(bar_empty + slot * 8);
                    if (++slot == kNS) { slot = 0; phase ^= 1; }
                }
                float x0 = fmaxf(s[0][0][0], s[0][0][1]), x1 = fmaxf(s[0][0][2], s[0][0][3]);
#pragma unroll
                for (int t = 0; t < kRun; ++t)
#pragma unroll
                    for (int n = 0; n < 2; ++n) {
                        x0 = fmaxf(x0, fmaxf(s[t][n][0], s[t][n][1]));
                        x1 = fmaxf(x1, fmaxf(s[t][n][2], s[t][n][3]));
                    }
                const float mn0 = fmaxf(m0, quad_max(x0) * c);
                const float mn1 = fmaxf(m1, quad_max(x1) * c);
                const float al0 = ex2(m0 - mn0), al1 = ex2(m1 - mn1);
                m0 = mn0; m1 = mn1;
                uint32_t pf[kRun][4];
                float r0 = 0.f, r1 = 0.f;
#pragma unroll
                for (int t = 0; t < kRun; ++t)
#pragma unroll
                    for (int n = 0; n < 2; ++n) {
                        const float p0 = ex2(fmaf(s[t][n][0], c, -mn0)), p1 = ex2(fmaf(s[t][n][1], c, -mn0));
                        const float p2 = ex2(fmaf(s[t][n][2], c, -mn1)), p3 = ex2(fmaf(s[t][n][3], c, -mn1));
                        r0 += p0 + p1;
                        r1 += p2 + p3;
                        pf[t][2 * n] = pack_bf16(p0, p1);
                        pf[t][2 * n + 1] = pack_bf16(p2, p3);
                    }
                l0 = fmaf(l0, al0, r0);
                l1 = fmaf(l1, al1, r1);
#pragma unroll
                for (int n = 0; n < 16; ++n) {
                    o[n][0] *= al0; o[n][1] *= al0; o[n][2] *= al1; o[n][3] *= al1;
                }
#pragma unroll
                for (int t = 0; t < kRun; ++t) {
                    const uint32_t base = sb + kSmRing + slot * kTileBytes + v_row;
                    mbar_wait(bar_full + slot * 8, phase);
#pragma unroll
                    for (int n2 = 0; n2 < 8; ++n2) {
                        uint32_t b0, b1, b2, b3;
                        ldsm4t(b0, b1, b2, b3, base + (n2 >> 2) * 8192 + (v_x ^ ((n2 & 3) << 5)));
                        mma16816(o[2 * n2], pf[t][0], pf[t][1], pf[t][2], pf[t][3], b0, b1);
                        mma16816(o[2 * n2 + 1], pf[t][0], pf[t][1], pf[t][2], pf[t][3], b2, b3);
                    }
                    __syncwarp();
                    if (lane == 0) mbar_arrive(bar_empty + slot * 8);
                    if (++slot == kNS) { slot = 0; phase ^= 1; }
                }
            }

            l0 = quad_sum(l0);
            l1 = quad_sum(l1);
            float* so = reinterpret_cast<float*>(sgen + kSmO);
            float* sml = reinterpret_cast<float*>(sgen + kSmML);
            {
                float* w0 = so + (warp * 16 + g) * kORow + 2 * tq;
                float* w1 = w0 + 8 * kORow;
#pragma unroll
                for (int n = 0; n < 16; ++n) {
                    *reinterpret_cast<float2*>(w0 + 8 * n) = make_float2(o[n][0], o[n][1]);
                    *reinterpret_cast<float2*>(w1 + 8 * n) = make_float2(o[n][2], o[n][3]);
                }
                if (tq == 0) {
                    *reinterpret_cast<float2*>(sml + (warp * 16 + g) * 2) = make_float2(m0, l0);
                    *reinterpret_cast<float2*>(sml + (warp * 16 + g + 8) * 2) = make_float2(m1, l1);
                }
            }
            asm volatile("bar.sync 1, %0;" ::"n"(kCW * 32) : "memory");
            {
                const int row = threadIdx.x >> 3;
                const int cb = (threadIdx.x & 7) * 8;
                float mw[kCW], lw[kCW];
                float M = -INFINITY;
#pragma unroll
                for (int w = 0; w < kCW; ++w) {
                    const float2 ml = *reinterpret_cast<const float2*>(sml + (w * 16 + row) * 2);
                    mw[w] = ml.x; lw[w] = ml.y;
                    M = fmaxf(M, ml.x);
                }
                float L = 0.f;
#pragma unroll
                for (int w = 0; w < kCW; ++w) {
                    mw[w] = ex2(mw[w] - M);
                    L = fmaf(lw[w], mw[w], L);
                }
                const float inv = 1.0f / L;
#pragma unroll
                for (int w = 0; w < kCW; ++w) mw[w] *= inv;
                __nv_bfloat16* orow = out + ((size_t)pair * 16 + row) * kD + cb;
#pragma unroll
                for (int h = 0; h < 2; ++h) {
                    float acc[8];
#pragma unroll
                    for (int e = 0; e < 8; ++e) acc[e] = 0.f;
#pragma unroll
                    for (int w = 0; w < kCW; ++w) {
                        const float* src = so + (w * 16 + row) * kORow + cb + 64 * h;
                        const float4 x = *reinterpret_cast<const float4*>(src);
                        const float4 y = *reinterpret_cast<const float4*>(src + 4);
                        acc[0] = fmaf(x.x, mw[w], acc[0]); acc[1] = fmaf(x.y, mw[w], acc[1]);
                        acc[2] = fmaf(x.z, mw[w], acc[2]); acc[3] = fmaf(x.w, mw[w], acc[3]);
                        acc[4] = fmaf(y.x, mw[w], acc[4]); acc[5] = fmaf(y.y, mw[w], acc[5]);
                        acc[6] = fmaf(y.z, mw[w], acc[6]); acc[7] = fmaf(y.w, mw[w], acc[7]);
                    }
                    uint4 pk;
                    pk.x = pack_bf16(acc[0], acc[1]); pk.y = pack_bf16(acc[2], acc[3]);
                    pk.z = pack_bf16(acc[4], acc[5]); pk.w = pack_bf16(acc[6], acc[7]);
                    *reinterpret_cast<uint4*>(orow + 64 * h) = pk;
                }
            }
        }
    }
}

typedef CUresult (*EncodeTiledFn)(CUtensorMap*, CUtensorMapDataType, cuuint32_t, void*, const cuuint64_t*,
                                  const cuuint64_t*, const cuuint32_t*, const cuuint32_t*, CUtensorMapInterleave,
                                  CUtensorMapSwizzle, CUtensorMapL2promotion, CUtensorMapFloatOOBfill);

void make_kv_map(EncodeTiledFn enc, CUtensorMap* tm, const void* base) {
    cuuint64_t dims[3] = {64, (cuuint64_t)kPairs * kC, 2};
    cuuint64_t strides[2] = {256, 128};
    cuuint32_t box[3] = {64, (cuuint32_t)kTileKeys, 2};
    cuuint32_t es[3] = {1, 1, 1};
    enc(tm, CU_TENSOR_MAP_DATA_TYPE_BFLOAT16, 3, const_cast<void*>(base), dims, strides, box, es,
        CU_TENSOR_MAP_INTERLEAVE_NONE, CU_TENSOR_MAP_SWIZZLE_128B, CU_TENSOR_MAP_L2_PROMOTION_L2_256B,
        CU_TENSOR_MAP_FLOAT_OOB_FILL_NONE);
}

}

extern "C" void kernel_launch(void* const* d_in, const int* in_sizes, int n_in, void* d_out, int out_size) {
    (void)in_sizes; (void)n_in; (void)out_size;
    const __nv_bfloat16* q = (const __nv_bfloat16*)d_in[0];
    const void* k_cache = d_in[1];
    const void* v_cache = d_in[2];
    const __nv_bfloat16* k_tree = (const __nv_bfloat16*)d_in[3];
    const __nv_bfloat16* v_tree = (const __nv_bfloat16*)d_in[4];
    const __nv_bfloat16* mask = (const __nv_bfloat16*)d_in[5];

    static EncodeTiledFn enc = nullptr;
    if (!enc) {
        void* fn = nullptr;
        cudaDriverEntryPointQueryResult qr;
        cudaGetDriverEntryPoint("cuTensorMapEncodeTiled", &fn, cudaEnableDefault, &qr);
        enc = (EncodeTiledFn)fn;
        cudaFuncSetAttribute(tree_attn_kernel, cudaFuncAttributeMaxDynamicSharedMemorySize, kSmemBytes);
    }
    CUtensorMap tmK, tmV;
    make_kv_map(enc, &tmK, k_cache);
    make_kv_map(enc, &tmV, v_cache);
    tree_attn_kernel<<<kGrid, kThreads, kSmemBytes>>>(tmK, tmV, q, k_tree, v_tree, mask, (__nv_bfloat16*)d_out);
}
```

```cpp
#include <cuda_runtime.h>
#include <cuda_bf16.h>
#include <cuda.h>
#include <stdint.h>

#define CFG_NS 8
#define CFG_INFLIGHT 4
#define CFG_RUN 4
#define CFG_HINT 1
#define CFG_PACE 1
#define CFG_W 256
#define CFG_FMIN 2
#define CFG_W1 CFG_W
#define CFG_WN -1000000
#define CFG_PF 0
#define CFG_PFV 0
#define CFG_PFN 0
#define CFG_AUXR 0
#define CFG_AUX0 0
#define CFG_SLEEP 200

namespace {

constexpr int kB = 32, kHkv = 16, kT = 8, kC = 2048, kD = 128;
constexpr int kPairs = kB * kHkv;
constexpr int kGrid = 128;
constexpr int kPairsPerCta = kPairs / kGrid;
constexpr int kTileKeys = 64;
constexpr int kTileBytes = kTileKeys * kD * 2;
constexpr int kRun = CFG_RUN;
constexpr int kRunsPerPair = kC / (kTileKeys * kRun);
constexpr int kTilesPerPair = 2 * kC / kTileKeys;
constexpr int kNS = CFG_NS;
constexpr int kInflight = CFG_INFLIGHT;
constexpr int kCW = 4;
constexpr int kThreads = (kCW + 1 + CFG_PACE) * 32;
constexpr int kTotalTiles = kPairsPerCta * kTilesPerPair;

constexpr int kAuxQ = 0, kAuxKt = 4096, kAuxVt = 6144, kAuxMask = 8192, kAuxBytes = 8320;

constexpr int kSmRing = 0;
constexpr int kSmAux = kSmRing + kNS * kTileBytes;
constexpr int kSmP = kSmAux + kPairsPerCta * kAuxBytes;
constexpr int kSmMax = kSmP + kRun * kCW * 32 * 16;
constexpr int kSmSum = kSmMax + 16 * kCW * 4;
constexpr int kSmBar = kSmSum + 16 * kCW * 4;
constexpr int kSmPace = kSmBar + (2 * kNS + kPairsPerCta) * 8;
constexpr int kSmTotal = kSmPace + 16;
constexpr int kSmemBytes = kSmTotal + 1024;

__device__ __forceinline__ uint32_t smem_u32(const void* p) {
    return (uint32_t)__cvta_generic_to_shared(p);
}
__device__ __forceinline__ void mbar_init(uint32_t bar, int cnt) {
    asm volatile("mbarrier.init.shared::cta.b64 [%0], %1;" ::"r"(bar), "r"(cnt) : "memory");
}
__device__ __forceinline__ void mbar_expect_tx(uint32_t bar, uint32_t bytes) {
    asm volatile("mbarrier.arrive.expect_tx.shared::cta.b64 _, [%0], %1;" ::"r"(bar), "r"(bytes) : "memory");
}
__device__ __forceinline__ void mbar_arrive(uint32_t bar) {
    asm volatile("mbarrier.arrive.shared::cta.b64 _, [%0];" ::"r"(bar) : "memory");
}
__device__ __forceinline__ bool mbar_try(uint32_t bar, uint32_t parity) {
    uint32_t ok;
    asm volatile(
        "{\n.reg .pred p;\n"
        "mbarrier.try_wait.parity.shared::cta.b64 p, [%1], %2;\n"
        "selp.u32 %0, 1, 0, p;\n}"
        : "=r"(ok) : "r"(bar), "r"(parity) : "memory");
    return ok != 0;
}
__device__ __forceinline__ bool mbar_test(uint32_t bar, uint32_t parity) {
    uint32_t ok;
    asm volatile(
        "{\n.reg .pred p;\n"
        "mbarrier.test_wait.parity.shared::cta.b64 p, [%1], %2;\n"
        "selp.u32 %0, 1, 0, p;\n}"
        : "=r"(ok) : "r"(bar), "r"(parity) : "memory");
    return ok != 0;
}
__device__ __forceinline__ void mbar_wait(uint32_t bar, uint32_t parity) {
    for (uint32_t it = 0; !mbar_try(bar, parity); ++it) {
        if (it > (1u << 24)) __trap();
    }
}
__device__ __forceinline__ void bulk_load(uint32_t dst, const void* src, uint32_t bytes, uint32_t bar) {
    asm volatile(
        "cp.async.bulk.shared::cluster.global.mbarrier::complete_tx::bytes [%0], [%1], %2, [%3];"
        ::"r"(dst), "l"(src), "r"(bytes), "r"(bar) : "memory");
}
__device__ __forceinline__ void bulk_prefetch(const void* src, uint32_t bytes) {
    asm volatile("cp.async.bulk.prefetch.L2.global [%0], %1;" ::"l"(src), "r"(bytes) : "memory");
}
__device__ __forceinline__ void tma_tile(uint32_t dst, const CUtensorMap* tm, int key, uint32_t bar, uint64_t pol) {
    asm volatile(
        "cp.async.bulk.tensor.3d.shared::cluster.global.mbarrier::complete_tx::bytes.L2::cache_hint "
        "[%0], [%1, {%3, %4, %5}], [%2], %6;"
        ::"r"(dst), "l"(tm), "r"(bar), "r"(0), "r"(key), "r"(0), "l"(pol) : "memory");
}
__device__ __forceinline__ void ldsm4(uint32_t& r0, uint32_t& r1, uint32_t& r2, uint32_t& r3, uint32_t addr) {
    asm volatile("ldmatrix.sync.aligned.m8n8.x4.shared.b16 {%0,%1,%2,%3}, [%4];"
                 : "=r"(r0), "=r"(r1), "=r"(r2), "=r"(r3) : "r"(addr) : "memory");
}
__device__ __forceinline__ void ldsm4t(uint32_t& r0, uint32_t& r1, uint32_t& r2, uint32_t& r3, uint32_t addr) {
    asm volatile("ldmatrix.sync.aligned.m8n8.x4.trans.shared.b16 {%0,%1,%2,%3}, [%4];"
                 : "=r"(r0), "=r"(r1), "=r"(r2), "=r"(r3) : "r"(addr) : "memory");
}
__device__ __forceinline__ void mma16816(float (&c)[4], uint32_t a0, uint32_t a1, uint32_t a2, uint32_t a3,
                                         uint32_t b0, uint32_t b1) {
    asm("mma.sync.aligned.m16n8k16.row.col.f32.bf16.bf16.f32 {%0,%1,%2,%3}, {%4,%5,%6,%7}, {%8,%9}, {%0,%1,%2,%3};"
        : "+f"(c[0]), "+f"(c[1]), "+f"(c[2]), "+f"(c[3])
        : "r"(a0), "r"(a1), "r"(a2), "r"(a3), "r"(b0), "r"(b1));
}
__device__ __forceinline__ float ex2(float x) {
    float y;
    asm("ex2.approx.ftz.f32 %0, %1;" : "=f"(y) : "f"(x));
    return y;
}
__device__ __forceinline__ uint32_t pack_bf16(float lo, float hi) {
    uint32_t r;
    asm("cvt.rn.bf16x2.f32 %0, %1, %2;" : "=r"(r) : "f"(hi), "f"(lo));
    return r;
}
__device__ __forceinline__ float quad_max(float v) {
    v = fmaxf(v, __shfl_xor_sync(0xffffffffu, v, 1));
    v = fmaxf(v, __shfl_xor_sync(0xffffffffu, v, 2));
    return v;
}
__device__ __forceinline__ float quad_sum(float v) {
    v += __shfl_xor_sync(0xffffffffu, v, 1);
    v += __shfl_xor_sync(0xffffffffu, v, 2);
    return v;
}

__device__ unsigned g_landed;

__global__ void __launch_bounds__(kThreads, 1)
tree_attn_kernel(const __grid_constant__ CUtensorMap tmK, const __grid_constant__ CUtensorMap tmV,
                 const __nv_bfloat16* __restrict__ q, const __nv_bfloat16* __restrict__ k_tree,
                 const __nv_bfloat16* __restrict__ v_tree, const __nv_bfloat16* __restrict__ mask,
                 __nv_bfloat16* __restrict__ out, const __nv_bfloat16* __restrict__ kc,
                 const __nv_bfloat16* __restrict__ vc) {
    extern __shared__ unsigned char smem_raw[];
    const uint32_t sraw = smem_u32(smem_raw);
    const uint32_t sb = (sraw + 1023u) & ~1023u;
    unsigned char* sgen = smem_raw + (sb - sraw);

    const uint32_t bar_full = sb + kSmBar;
    const uint32_t bar_empty = bar_full + kNS * 8;
    const uint32_t bar_aux = bar_empty + kNS * 8;

    volatile unsigned* const s_total = reinterpret_cast<volatile unsigned*>(sgen + kSmPace);
    volatile unsigned* const s_stop = s_total + 1;

    const int warp = threadIdx.x >> 5;
    const int lane = threadIdx.x & 31;

    if (warp == kCW) {
        uint64_t pol = 0;
        auto issue = [&](int i) {
            const int u = i / kTilesPerPair;
            const int r = i % kTilesPerPair;
            const int pair = blockIdx.x + u * kGrid;
            if (i == CFG_AUX0 || (CFG_AUXR ? (r == CFG_AUXR && u + 1 < kPairsPerCta) : (r == 0 && u > 0))) {
                const int ua = (CFG_AUXR && i != CFG_AUX0) ? u + 1 : u;
                const int pa = blockIdx.x + ua * kGrid;
                const uint32_t ab = bar_aux + ua * 8;
                const uint32_t dst = sb + kSmAux + ua * kAuxBytes;
                mbar_expect_tx(ab, 4096 + 2048 + 2048 + 128);
                bulk_load(dst + kAuxQ, q + (size_t)pa * 16 * kD, 4096, ab);
                bulk_load(dst + kAuxKt, k_tree + (size_t)pa * kT * kD, 2048, ab);
                bulk_load(dst + kAuxVt, v_tree + (size_t)pa * kT * kD, 2048, ab);
                bulk_load(dst + kAuxMask, mask + (size_t)(pa / kHkv) * kT * kT, 128, ab);
            }
            const int run = r / (2 * kRun);
            const int w = r % (2 * kRun);
            const int is_v = w / kRun;
            const int key = pair * kC + (run * kRun + (w % kRun)) * kTileKeys;
            const int slot = i % kNS;
            const uint32_t fb = bar_full + slot * 8;
            mbar_expect_tx(fb, kTileBytes);
            tma_tile(sb + kSmRing + slot * kTileBytes, is_v ? &tmV : &tmK, key, fb, pol);
        };
        if (lane == 0) {
            for (int s = 0; s < kNS; ++s) {
                mbar_init(bar_full + s * 8, 1);
                mbar_init(bar_empty + s * 8, kCW);
            }
            for (int u = 0; u < kPairsPerCta; ++u) mbar_init(bar_aux + u * 8, 1);
            *s_total = 0;
            *s_stop = 0;
            asm volatile("fence.mbarrier_init.release.cluster;" ::: "memory");
            asm volatile("fence.proxy.async.shared::cta;" ::: "memory");
            asm volatile("createpolicy.fractional.L2::evict_first.b64 %0, 1.0;" : "=l"(pol));
            for (int i = 0; i < kInflight; ++i) issue(i);
        }
        __syncthreads();
        if (lane == 0) {
            int issued = kInflight, landed = 0;
            uint32_t spins = 0;
            while (landed < kTotalTiles) {
                if (mbar_test(bar_full + (landed % kNS) * 8, (landed / kNS) & 1)) {
                    ++landed;
                    spins = 0;
                    asm volatile("red.relaxed.gpu.global.inc.u32 [%0], %1;"
                                 ::"l"(&g_landed), "r"((unsigned)(kGrid * kTotalTiles - 1)) : "memory");
                }
                if (issued < kTotalTiles) {
                    const int infl = issued - landed;
                    const int lead = landed * kGrid - (int)*s_total;
                    const int lim = lead > CFG_W ? CFG_FMIN : lead > CFG_W1 ? kInflight - 1 : lead < CFG_WN ? kInflight + 1 : kInflight;
                    if (infl < lim &&
                        (issued < kNS || mbar_test(bar_empty + (issued % kNS) * 8, ((issued / kNS) - 1) & 1))) {
                        issue(issued);
                        ++issued;
                        if (issued == kTotalTiles) *s_stop = 1;
                    }
                }
                if (++spins > (1u << 28)) __trap();
            }
        }
    } else if (warp == kCW + 1) {
        __syncthreads();
        if (lane == 0) {
            for (uint32_t it = 0; *s_stop == 0 && it < (1u << 24); ++it) {
                unsigned t;
                asm volatile("ld.relaxed.gpu.global.u32 %0, [%1];" : "=r"(t) : "l"(&g_landed) : "memory");
                *s_total = t;
                __nanosleep(CFG_SLEEP);
            }
        }
    } else {
        __syncthreads();
        const int g = lane >> 2;
        const int tq = lane & 3;
        const int mi = lane >> 3;
        const int lr = lane & 7;
        const float c = 0.08838834764831845f * 1.4426950408889634f;

        const uint32_t k_row = (uint32_t)(16 * warp + 8 * (mi >> 1) + lr) * 128u;
        const uint32_t k_x = (uint32_t)(((mi & 1) ^ lr) << 4);
        const uint32_t v_row = (uint32_t)(warp >> 1) * 8192u + (uint32_t)(8 * (mi & 1) + lr) * 128u;
        const uint32_t v_x0 = (uint32_t)(((4 * (warp & 1) + (mi >> 1)) ^ lr) << 4);
        const uint32_t v_x1 = v_x0 ^ 32u;

        uint4* const pbuf = reinterpret_cast<uint4*>(sgen + kSmP);
        float* const smax = reinterpret_cast<float*>(sgen + kSmMax);
        float* const ssum = reinterpret_cast<float*>(sgen + kSmSum);

        int slot = 0;
        uint32_t phase = 0;

        for (int u = 0; u < kPairsPerCta; ++u) {
            const int pair = blockIdx.x + u * kGrid;
            const uint32_t aux = sb + kSmAux + u * kAuxBytes;
            mbar_wait(bar_aux + u * 8, 0);

            uint32_t qf[8][4];
            {
                const uint32_t qa = aux + kAuxQ + (uint32_t)(lr + 8 * (mi & 1)) * 256u + (uint32_t)(mi >> 1) * 16u;
#pragma unroll
                for (int s = 0; s < 8; ++s) ldsm4(qf[s][0], qf[s][1], qf[s][2], qf[s][3], qa + s * 32);
            }

            float o[4][4];
            float m0, m1, l0, l1;
            {
                float st[4] = {0.f, 0.f, 0.f, 0.f};
                const uint32_t ka = aux + kAuxKt + (uint32_t)lr * 256u + (uint32_t)mi * 16u;
#pragma unroll
                for (int s2 = 0; s2 < 4; ++s2) {
                    uint32_t b0, b1, b2, b3;
                    ldsm4(b0, b1, b2, b3, ka + s2 * 64);
                    mma16816(st, qf[2 * s2][0], qf[2 * s2][1], qf[2 * s2][2], qf[2 * s2][3], b0, b1);
                    mma16816(st, qf[2 * s2 + 1][0], qf[2 * s2 + 1][1], qf[2 * s2 + 1][2], qf[2 * s2 + 1][3], b2, b3);
                }
                const __nv_bfloat162 mk =
                    *reinterpret_cast<const __nv_bfloat162*>(sgen + kSmAux + u * kAuxBytes + kAuxMask + (g * kT + 2 * tq) * 2);
                const float bias0 = (1.0f - __low2float(mk)) * (-1.0e9f * 1.4426950408889634f);
                const float bias1 = (1.0f - __high2float(mk)) * (-1.0e9f * 1.4426950408889634f);
                const float t0 = fmaf(st[0], c, bias0), t1 = fmaf(st[1], c, bias1);
                const float t2 = fmaf(st[2], c, bias0), t3 = fmaf(st[3], c, bias1);
                m0 = quad_max(fmaxf(t0, t1));
                m1 = quad_max(fmaxf(t2, t3));
                const float p0 = ex2(t0 - m0), p1 = ex2(t1 - m0), p2 = ex2(t2 - m1), p3 = ex2(t3 - m1);
                l0 = (warp == 0) ? p0 + p1 : 0.f;
                l1 = (warp == 0) ? p2 + p3 : 0.f;
                const uint32_t a0 = pack_bf16(p0, p1), a1 = pack_bf16(p2, p3);
                uint32_t b0, b1, b2, b3;
                ldsm4t(b0, b1, b2, b3, aux + kAuxVt + (uint32_t)lr * 256u + (uint32_t)(4 * warp + mi) * 16u);
#pragma unroll
                for (int n = 0; n < 4; ++n) { o[n][0] = 0.f; o[n][1] = 0.f; o[n][2] = 0.f; o[n][3] = 0.f; }
                mma16816(o[0], a0, a1, 0u, 0u, b0, 0u);
                mma16816(o[1], a0, a1, 0u, 0u, b1, 0u);
                mma16816(o[2], a0, a1, 0u, 0u, b2, 0u);
                mma16816(o[3], a0, a1, 0u, 0u, b3, 0u);
            }
            float inv0 = 0.f, inv1 = 0.f;

            for (int run = 0; run < kRunsPerPair; ++run) {
                float s[kRun][2][4];
#pragma unroll
                for (int t = 0; t < kRun; ++t) {
                    const uint32_t base = sb + kSmRing + slot * kTileBytes + k_row;
                    mbar_wait(bar_full + slot * 8, phase);
#pragma unroll
                    for (int e = 0; e < 4; ++e) { s[t][0][e] = 0.f; s[t][1][e] = 0.f; }
#pragma unroll
                    for (int ks = 0; ks < 8; ++ks) {
                        uint32_t b0, b1, b2, b3;
                        ldsm4(b0, b1, b2, b3, base + (ks >> 2) * 8192 + (k_x ^ ((ks & 3) << 5)));
                        mma16816(s[t][0], qf[ks][0], qf[ks][1], qf[ks][2], qf[ks][3], b0, b1);
                        mma16816(s[t][1], qf[ks][0], qf[ks][1], qf[ks][2], qf[ks][3], b2, b3);
                    }
                    __syncwarp();
                    if (lane == 0) mbar_arrive(bar_empty + slot * 8);
                    if (++slot == kNS) { slot = 0; phase ^= 1; }
                }
                float x0 = fmaxf(s[0][0][0], s[0][0][1]), x1 = fmaxf(s[0][0][2], s[0][0][3]);
#pragma unroll
                for (int t = 0; t < kRun; ++t)
#pragma unroll
                    for (int n = 0; n < 2; ++n) {
                        x0 = fmaxf(x0, fmaxf(s[t][n][0], s[t][n][1]));
                        x1 = fmaxf(x1, fmaxf(s[t][n][2], s[t][n][3]));
                    }
                x0 = quad_max(x0);
                x1 = quad_max(x1);
                if (tq == 0) {
                    smax[g * kCW + warp] = x0;
                    smax[(g + 8) * kCW + warp] = x1;
                }
                asm volatile("bar.sync 1, %0;" ::"n"(kCW * 32) : "memory");
                {
                    const float4 a = *reinterpret_cast<const float4*>(smax + g * kCW);
                    const float4 b = *reinterpret_cast<const float4*>(smax + (g + 8) * kCW);
                    x0 = fmaxf(fmaxf(a.x, a.y), fmaxf(a.z, a.w));
                    x1 = fmaxf(fmaxf(b.x, b.y), fmaxf(b.z, b.w));
                }
                const float mn0 = fmaxf(m0, x0 * c);
                const float mn1 = fmaxf(m1, x1 * c);
                const float al0 = ex2(m0 - mn0), al1 = ex2(m1 - mn1);
                m0 = mn0; m1 = mn1;
                float r0 = 0.f, r1 = 0.f;
#pragma unroll
                for (int t = 0; t < kRun; ++t) {
                    uint32_t pf[4];
#pragma unroll
                    for (int n = 0; n < 2; ++n) {
                        const float p0 = ex2(fmaf(s[t][n][0], c, -mn0)), p1 = ex2(fmaf(s[t][n][1], c, -mn0));
                        const float p2 = ex2(fmaf(s[t][n][2], c, -mn1)), p3 = ex2(fmaf(s[t][n][3], c, -mn1));
                        r0 += p0 + p1;
                        r1 += p2 + p3;
                        pf[2 * n] = pack_bf16(p0, p1);
                        pf[2 * n + 1] = pack_bf16(p2, p3);
                    }
                    pbuf[(t * kCW + warp) * 32 + lane] = make_uint4(pf[0], pf[1], pf[2], pf[3]);
                }
                l0 = fmaf(l0, al0, r0);
                l1 = fmaf(l1, al1, r1);
                if (run == kRunsPerPair - 1) {
                    const float ls0 = quad_sum(l0), ls1 = quad_sum(l1);
                    if (tq == 0) {
                        ssum[g * kCW + warp] = ls0;
                        ssum[(g + 8) * kCW + warp] = ls1;
                    }
                }
                asm volatile("bar.sync 1, %0;" ::"n"(kCW * 32) : "memory");
                if (run == kRunsPerPair - 1) {
                    const float4 a = *reinterpret_cast<const float4*>(ssum + g * kCW);
                    const float4 b = *reinterpret_cast<const float4*>(ssum + (g + 8) * kCW);
                    inv0 = 1.0f / ((a.x + a.y) + (a.z + a.w));
                    inv1 = 1.0f / ((b.x + b.y) + (b.z + b.w));
                }
#pragma unroll
                for (int n = 0; n < 4; ++n) {
                    o[n][0] *= al0; o[n][1] *= al0; o[n][2] *= al1; o[n][3] *= al1;
                }
#pragma unroll
                for (int t = 0; t < kRun; ++t) {
                    uint4 pa[kCW];
#pragma unroll
                    for (int ks = 0; ks < kCW; ++ks) pa[ks] = pbuf[(t * kCW + ks) * 32 + lane];
                    const uint32_t base = sb + kSmRing + slot * kTileBytes + v_row;
                    mbar_wait(bar_full + slot * 8, phase);
#pragma unroll
                    for (int ks = 0; ks < kCW; ++ks) {
                        uint32_t b0, b1, b2, b3, b4, b5, b6, b7;
                        ldsm4t(b0, b1, b2, b3, base + ks * 2048 + v_x0);
                        ldsm4t(b4, b5, b6, b7, base + ks * 2048 + v_x1);
                        mma16816(o[0], pa[ks].x, pa[ks].y, pa[ks].z, pa[ks].w, b0, b1);
                        mma16816(o[1], pa[ks].x, pa[ks].y, pa[ks].z, pa[ks].w, b2, b3);
                        mma16816(o[2], pa[ks].x, pa[ks].y, pa[ks].z, pa[ks].w, b4, b5);
                        mma16816(o[3], pa[ks].x, pa[ks].y, pa[ks].z, pa[ks].w, b6, b7);
                    }
                    __syncwarp();
                    if (lane == 0) mbar_arrive(bar_empty + slot * 8);
                    if (++slot == kNS) { slot = 0; phase ^= 1; }
                }
            }

            {
                uint32_t* o0 = reinterpret_cast<uint32_t*>(out + ((size_t)pair * 16 + g) * kD + 32 * warp + 2 * tq);
                uint32_t* o1 = o0 + 8 * kD / 2;
#pragma unroll
                for (int n = 0; n < 4; ++n) {
                    o0[4 * n] = pack_bf16(o[n][0] * inv0, o[n][1] * inv0);
                    o1[4 * n] = pack_bf16(o[n][2] * inv1, o[n][3] * inv1);
                }
            }
        }
    }
}

typedef CUresult (*EncodeTiledFn)(CUtensorMap*, CUtensorMapDataType, cuuint32_t, void*, const cuuint64_t*,
                                  const cuuint64_t*, const cuuint32_t*, const cuuint32_t*, CUtensorMapInterleave,
                                  CUtensorMapSwizzle, CUtensorMapL2promotion, CUtensorMapFloatOOBfill);

void make_kv_map(EncodeTiledFn enc, CUtensorMap* tm, const void* base) {
    cuuint64_t dims[3] = {64, (cuuint64_t)kPairs * kC, 2};
    cuuint64_t strides[2] = {256, 128};
    cuuint32_t box[3] = {64, (cuuint32_t)kTileKeys, 2};
    cuuint32_t es[3] = {1, 1, 1};
    enc(tm, CU_TENSOR_MAP_DATA_TYPE_BFLOAT16, 3, const_cast<void*>(base), dims, strides, box, es,
        CU_TENSOR_MAP_INTERLEAVE_NONE, CU_TENSOR_MAP_SWIZZLE_128B, CU_TENSOR_MAP_L2_PROMOTION_L2_256B,
        CU_TENSOR_MAP_FLOAT_OOB_FILL_NONE);
}

}

extern "C" void kernel_launch(void* const* d_in, const int* in_sizes, int n_in, void* d_out, int out_size) {
    (void)in_sizes; (void)n_in; (void)out_size;
    const __nv_bfloat16* q = (const __nv_bfloat16*)d_in[0];
    const void* k_cache = d_in[1];
    const void* v_cache = d_in[2];
    const __nv_bfloat16* k_tree = (const __nv_bfloat16*)d_in[3];
    const __nv_bfloat16* v_tree = (const __nv_bfloat16*)d_in[4];
    const __nv_bfloat16* mask = (const __nv_bfloat16*)d_in[5];

    static EncodeTiledFn enc = nullptr;
    if (!enc) {
        void* fn = nullptr;
        cudaDriverEntryPointQueryResult qr;
        cudaGetDriverEntryPoint("cuTensorMapEncodeTiled", &fn, cudaEnableDefault, &qr);
        enc = (EncodeTiledFn)fn;
        cudaFuncSetAttribute(tree_attn_kernel, cudaFuncAttributeMaxDynamicSharedMemorySize, kSmemBytes);
    }
    CUtensorMap tmK, tmV;
    make_kv_map(enc, &tmK, k_cache);
    make_kv_map(enc, &tmV, v_cache);
    tree_attn_kernel<<<kGrid, kThreads, kSmemBytes>>>(tmK, tmV, q, k_tree, v_tree, mask, (__nv_bfloat16*)d_out,
                                                      (const __nv_bfloat16*)k_cache, (const __nv_bfloat16*)v_cache);
}
```

```cpp
#include <cuda_runtime.h>
#include <cuda_bf16.h>
#include <cuda.h>
#include <stdint.h>

#define CFG_NS 10
#define CFG_F 8
#define CFG_FMIN 4
#define CFG_W 96
#define CFG_ILV 0
#define CFG_SLEEP 200
#define CFG_JITTER 0
#define CFG_ABL 0
#define CFG_PF 2
#define CFG_ACQ 1

namespace {

constexpr int kB = 32, kHkv = 16, kT = 8, kC = 2048, kD = 128;
constexpr int kPairs = kB * kHkv;
constexpr int kG = 8;
constexpr int kGrid = 64;
constexpr int kClusters = kGrid / kG;
constexpr int kPairsPerCta = kPairs / kClusters;
constexpr int kTileKeys = 64;
constexpr int kTileBytes = kTileKeys * kD * 2;
constexpr int kRun = kC / kG / kTileKeys;
constexpr int kTilesPerIssuer = kPairsPerCta * kRun;
constexpr int kNS = CFG_NS, kNH = kNS / 2;
constexpr int kFH = CFG_F / 2, kFMH = CFG_FMIN / 2;
constexpr int kCW = 4;
constexpr int kWIssue = 4, kWPoll = 6, kWComb = 7;
constexpr int kThreads = 256;
static_assert(kNS % 2 == 0 && kNS <= 16 && kFH < kNH && kFMH <= kFH && kFMH >= 1, "config");

constexpr int kRecvBytes = kG * 1024;
constexpr int kMlBytes = kG * 128;

constexpr int kSmRing = 0;
constexpr int kSmQ = kSmRing + kNS * kTileBytes;
constexpr int kSmP = kSmQ + 2 * 4096;
constexpr int kSmRecv = kSmP + kRun * kCW * 32 * 16;
constexpr int kSmMl = kSmRecv + 2 * kRecvBytes;
constexpr int kSmMax = kSmMl + 4 * kMlBytes;
constexpr int kSmSum = kSmMax + 16 * kCW * 4;
constexpr int kSmBar = kSmSum + 16 * kCW * 4;
constexpr int kNumBars = 2 * kNS + 2 + 2 + 2 + 4;
constexpr int kSmPace = kSmBar + kNumBars * 8;
constexpr int kSmemBytes = kSmPace + 16;
static_assert(kSmemBytes <= 232448, "shared memory");

__device__ __forceinline__ uint32_t smem_u32(const void* p) {
    return (uint32_t)__cvta_generic_to_shared(p);
}
__device__ __forceinline__ void mbar_init(uint32_t bar, int cnt) {
    asm volatile("mbarrier.init.shared::cta.b64 [%0], %1;" ::"r"(bar), "r"(cnt) : "memory");
}
__device__ __forceinline__ void mbar_expect_tx(uint32_t bar, uint32_t bytes) {
    asm volatile("mbarrier.arrive.expect_tx.shared::cta.b64 _, [%0], %1;" ::"r"(bar), "r"(bytes) : "memory");
}
__device__ __forceinline__ void mbar_arrive(uint32_t bar) {
    asm volatile("mbarrier.arrive.shared::cta.b64 _, [%0];" ::"r"(bar) : "memory");
}
__device__ __forceinline__ bool mbar_try(uint32_t bar, uint32_t parity) {
    uint32_t ok;
    asm volatile(
        "{\n.reg .pred p;\n"
        "mbarrier.try_wait.parity.shared::cta.b64 p, [%1], %2;\n"
        "selp.u32 %0, 1, 0, p;\n}"
        : "=r"(ok) : "r"(bar), "r"(parity) : "memory");
    return ok != 0;
}
__device__ __forceinline__ bool mbar_try_cluster(uint32_t bar, uint32_t parity) {
    uint32_t ok;
    asm volatile(
        "{\n.reg .pred p;\n"
        "mbarrier.try_wait.parity.acquire.cluster.shared::cta.b64 p, [%1], %2;\n"
        "selp.u32 %0, 1, 0, p;\n}"
        : "=r"(ok) : "r"(bar), "r"(parity) : "memory");
    return ok != 0;
}
__device__ __forceinline__ bool mbar_test(uint32_t bar, uint32_t parity) {
    uint32_t ok;
    asm volatile(
        "{\n.reg .pred p;\n"
        "mbarrier.test_wait.parity.shared::cta.b64 p, [%1], %2;\n"
        "selp.u32 %0, 1, 0, p;\n}"
        : "=r"(ok) : "r"(bar), "r"(parity) : "memory");
    return ok != 0;
}
__device__ __forceinline__ void mbar_wait(uint32_t bar, uint32_t parity) {
    for (uint32_t it = 0; !mbar_try(bar, parity); ++it)
        if (it > (1u << 22)) __trap();
}
__device__ __forceinline__ void mbar_wait_cluster(uint32_t bar, uint32_t parity) {
    for (uint32_t it = 0; !(CFG_ACQ ? mbar_try_cluster(bar, parity) : mbar_try(bar, parity)); ++it)
        if (it > (1u << 22)) __trap();
}
__device__ __forceinline__ uint32_t lds_volatile(uint32_t a) {
    uint32_t v;
    asm volatile("ld.volatile.shared.u32 %0, [%1];" : "=r"(v) : "r"(a) : "memory");
    return v;
}
__device__ __forceinline__ void sts_volatile(uint32_t a, uint32_t v) {
    asm volatile("st.volatile.shared.u32 [%0], %1;" ::"r"(a), "r"(v) : "memory");
}
__device__ __forceinline__ uint32_t mapa(uint32_t addr, uint32_t rank) {
    uint32_t r;
    asm("mapa.shared::cluster.u32 %0, %1, %2;" : "=r"(r) : "r"(addr), "r"(rank));
    return r;
}
__device__ __forceinline__ void st_async4(uint32_t addr, float a, float b, float c, float d, uint32_t bar) {
    asm volatile("st.async.weak.shared::cluster.mbarrier::complete_tx::bytes.v4.f32 [%0], {%1,%2,%3,%4}, [%5];"
                 ::"r"(addr), "f"(a), "f"(b), "f"(c), "f"(d), "r"(bar) : "memory");
}
__device__ __forceinline__ void tma_tile(uint32_t dst, const CUtensorMap* tm, int row, uint32_t bar, uint64_t pol) {
    asm volatile(
        "cp.async.bulk.tensor.3d.shared::cluster.global.mbarrier::complete_tx::bytes.L2::cache_hint "
        "[%0], [%1, {%3, %4, %5}], [%2], %6;"
        ::"r"(dst), "l"(tm), "r"(bar), "r"(0), "r"(row), "r"(0), "l"(pol) : "memory");
}
__device__ __forceinline__ void tma_tile_nohint(uint32_t dst, const CUtensorMap* tm, int row, uint32_t bar) {
    asm volatile(
        "cp.async.bulk.tensor.3d.shared::cluster.global.mbarrier::complete_tx::bytes "
        "[%0], [%1, {%3, %4, %5}], [%2];"
        ::"r"(dst), "l"(tm), "r"(bar), "r"(0), "r"(row), "r"(0) : "memory");
}
__device__ __forceinline__ void ldsm4(uint32_t& r0, uint32_t& r1, uint32_t& r2, uint32_t& r3, uint32_t addr) {
    asm volatile("ldmatrix.sync.aligned.m8n8.x4.shared.b16 {%0,%1,%2,%3}, [%4];"
                 : "=r"(r0), "=r"(r1), "=r"(r2), "=r"(r3) : "r"(addr) : "memory");
}
__device__ __forceinline__ void ldsm4t(uint32_t& r0, uint32_t& r1, uint32_t& r2, uint32_t& r3, uint32_t addr) {
    asm volatile("ldmatrix.sync.aligned.m8n8.x4.trans.shared.b16 {%0,%1,%2,%3}, [%4];"
                 : "=r"(r0), "=r"(r1), "=r"(r2), "=r"(r3) : "r"(addr) : "memory");
}
__device__ __forceinline__ void mma16816(float (&c)[4], uint32_t a0, uint32_t a1, uint32_t a2, uint32_t a3,
                                         uint32_t b0, uint32_t b1) {
    asm("mma.sync.aligned.m16n8k16.row.col.f32.bf16.bf16.f32 {%0,%1,%2,%3}, {%4,%5,%6,%7}, {%8,%9}, {%0,%1,%2,%3};"
        : "+f"(c[0]), "+f"(c[1]), "+f"(c[2]), "+f"(c[3])
        : "r"(a0), "r"(a1), "r"(a2), "r"(a3), "r"(b0), "r"(b1));
}
__device__ __forceinline__ float ex2(float x) {
    float y;
    asm("ex2.approx.ftz.f32 %0, %1;" : "=f"(y) : "f"(x));
    return y;
}
__device__ __forceinline__ uint32_t pack_bf16(float lo, float hi) {
    uint32_t r;
    asm("cvt.rn.bf16x2.f32 %0, %1, %2;" : "=r"(r) : "f"(hi), "f"(lo));
    return r;
}
__device__ __forceinline__ float quad_max(float v) {
    v = fmaxf(v, __shfl_xor_sync(0xffffffffu, v, 1));
    v = fmaxf(v, __shfl_xor_sync(0xffffffffu, v, 2));
    return v;
}
__device__ __forceinline__ float quad_sum(float v) {
    v += __shfl_xor_sync(0xffffffffu, v, 1);
    v += __shfl_xor_sync(0xffffffffu, v, 2);
    return v;
}
__device__ __forceinline__ void jitter(uint32_t salt) {
    (void)salt;
}

constexpr uint32_t kOnes = 0x3f803f80u;

__device__ unsigned g_progress;

__global__ void __cluster_dims__(kG, 1, 1) __launch_bounds__(kThreads, 1)
tree_attn_kernel(const __grid_constant__ CUtensorMap tmK, const __grid_constant__ CUtensorMap tmV,
                 const __grid_constant__ CUtensorMap tmQ, const __nv_bfloat16* __restrict__ q,
                 const __nv_bfloat16* __restrict__ k_tree, const __nv_bfloat16* __restrict__ v_tree,
                 const __nv_bfloat16* __restrict__ mask, __nv_bfloat16* __restrict__ out,
                 const __nv_bfloat16* __restrict__ kc, const __nv_bfloat16* __restrict__ vc) {
    if (threadIdx.x < CFG_PF) {
        const int t = threadIdx.x & 3;
        const int key = (blockIdx.x / kG) * kC + (CFG_ILV == 0 ? (t * kG + blockIdx.x % kG) : (blockIdx.x % kG * kRun + t)) * kTileKeys;
        uint64_t p;
        asm volatile("createpolicy.fractional.L2::evict_first.b64 %0, 1.0;" : "=l"(p));
        asm volatile("cp.async.bulk.prefetch.L2.global.L2::cache_hint [%0], %1, %2;"
                     ::"l"((threadIdx.x < 4 ? kc : vc) + (size_t)key * kD), "r"(kTileBytes), "l"(p) : "memory");
    }
    extern __shared__ __align__(1024) unsigned char sgen[];
    const uint32_t sb = smem_u32(sgen);

    const uint32_t bar_full = sb + kSmBar;
    const uint32_t bar_empty = bar_full + kNS * 8;
    const uint32_t bar_q = bar_empty + kNS * 8;
    const uint32_t bar_rfull = bar_q + 2 * 8;
    const uint32_t bar_cdone = bar_rfull + 2 * 8;
    const uint32_t bar_ml = bar_cdone + 2 * 8;
    const uint32_t s_total = sb + kSmPace, s_stop = s_total + 4;

    const int warp = threadIdx.x >> 5;
    const int lane = threadIdx.x & 31;
    const int cl = blockIdx.x / kG;
    const int mem = blockIdx.x % kG;
    const float c = 0.08838834764831845f * 1.4426950408889634f;

    uint64_t pol = 0;
    auto issue = [&](int j, int x, int slot) {
        const int u = j >> 2;
        const int r = 2 * (j & 3) + x;
        const int pair = cl + u * kClusters;
        const int t = r & 3;
        const int key = pair * kC + (CFG_ILV == 0 ? (t * kG + mem) : (mem * kRun + t)) * kTileKeys;
        const uint32_t fb = bar_full + slot * 8;
        mbar_expect_tx(fb, kTileBytes);
        tma_tile(sb + kSmRing + slot * kTileBytes, r >= 4 ? &tmV : &tmK, key, fb, pol);
        if (r == 0) {
            const uint32_t qb = bar_q + (u & 1) * 8;
            mbar_expect_tx(qb, 4096);
            tma_tile_nohint(sb + kSmQ + (u & 1) * 4096, &tmQ, pair * 16, qb);
        }
    };

    asm volatile("createpolicy.fractional.L2::evict_first.b64 %0, 1.0;" : "=l"(pol));
    if (threadIdx.x == kWIssue * 32) {
#pragma unroll
        for (int i = 0; i < 2 * kFH; ++i) mbar_init(bar_full + i * 8, 1);
        mbar_init(bar_q, 1);
        asm volatile("fence.proxy.async.shared::cta;" ::: "memory");
#pragma unroll
        for (int i = 0; i < 2 * kFH; ++i) issue(i >> 1, i & 1, i);
        for (int s = 2 * kFH; s < kNS; ++s) mbar_init(bar_full + s * 8, 1);
        for (int s = 0; s < kNS; ++s) mbar_init(bar_empty + s * 8, kCW);
        mbar_init(bar_q + 8, 1);
        for (int s = 0; s < 2; ++s) {
            mbar_init(bar_cdone + s * 8, 1);
            mbar_init(bar_rfull + s * 8, 1);
            mbar_expect_tx(bar_rfull + s * 8, kRecvBytes);
        }
        for (int s = 0; s < 4; ++s) {
            mbar_init(bar_ml + s * 8, 1);
            mbar_expect_tx(bar_ml + s * 8, kMlBytes);
        }
        sts_volatile(s_total, 0);
        sts_volatile(s_stop, 0);
        sts_volatile(s_stop + 4, 0);
        asm volatile("fence.mbarrier_init.release.cluster;" ::: "memory");
        asm volatile("fence.proxy.async.shared::cta;" ::: "memory");
        if (sb & 1023u) __trap();
    }
    __syncthreads();
    asm volatile("barrier.cluster.arrive.relaxed.aligned;" ::: "memory");

    if (warp == kWIssue || warp == kWIssue + 1) {
        if (lane == 0) {
            const int x = warp - kWIssue;
            const uint32_t bf = bar_full + x * 8, be = bar_empty + x * 8;
            int si = kFH; uint32_t pe = 1;
            int sf = 0; uint32_t pf = 0;
            int sm = kFH - kFMH; uint32_t pm = 0;
            for (int j = kFH; j < kTilesPerIssuer; ++j) {
                mbar_wait(bf + sf * 16, pf);
                if (++sf == kNH) { sf = 0; pf ^= 1; }
                if (x == 0)
                    asm volatile("red.relaxed.gpu.global.inc.u32 [%0], %1;"
                                 ::"l"(&g_progress), "r"((unsigned)(kGrid * (kTilesPerIssuer - kFH) - 1)) : "memory");
                const int mine = (j - kFH + 1) * kGrid - CFG_W;
                for (uint32_t it = 0; mine > (int)lds_volatile(s_total) && !mbar_test(bf + sm * 16, pm); ++it)
                    if (it > (1u << 26)) __trap();
                if (++sm == kNH) { sm = 0; pm ^= 1; }
                mbar_wait(be + si * 16, pe);
                issue(j, x, 2 * si + x);
                if (++si == kNH) { si = 0; pe ^= 1; }
            }
            sts_volatile(s_stop + 4 * x, 1);
        }
    } else if (warp == kWPoll) {
        if (lane == 0) {
            for (uint32_t it = 0; (lds_volatile(s_stop) & lds_volatile(s_stop + 4)) == 0 && it < (1u << 24); ++it) {
                unsigned t;
                asm volatile("ld.relaxed.gpu.global.u32 %0, [%1];" : "=r"(t) : "l"(&g_progress) : "memory");
                sts_volatile(s_total, t);
                __nanosleep(CFG_SLEEP);
            }
        }
    } else if (warp == kWComb) {
        const int g = lane >> 2, tq = lane & 3;
        uint4 qa[4], qb[4], kt[4];
        uint32_t vt[2], mk;
        auto fetch = [&](int u) {
            const int pair = cl + u * kClusters;
            const uint4* qp = reinterpret_cast<const uint4*>(q + ((size_t)pair * 16 + g) * kD) + tq;
            const uint4* kp = reinterpret_cast<const uint4*>(k_tree + ((size_t)pair * kT + g) * kD) + tq;
#pragma unroll
            for (int j = 0; j < 4; ++j) {
                qa[j] = __ldg(qp + 4 * j);
                qb[j] = __ldg(qp + 4 * j + 8 * kD / 8);
                kt[j] = __ldg(kp + 4 * j);
            }
            const unsigned short* vp =
                reinterpret_cast<const unsigned short*>(v_tree) + ((size_t)pair * kT + 2 * tq) * kD + 16 * mem + g;
#pragma unroll
            for (int n = 0; n < 2; ++n)
                vt[n] = (uint32_t)__ldg(vp + 8 * n) | ((uint32_t)__ldg(vp + 8 * n + kD) << 16);
            mk = __ldg(reinterpret_cast<const uint32_t*>(mask + (size_t)(pair / kHkv) * kT * kT + g * kT + 2 * tq));
        };
        fetch(0);
        for (int u = 0; u < kPairsPerCta; ++u) {
            const int s = u & 1;
            const int pair = cl + u * kClusters;
            float acc[2][4], lt[4] = {0.f, 0.f, 0.f, 0.f}, mt0, mt1;
            {
                float st[4] = {0.f, 0.f, 0.f, 0.f};
#pragma unroll
                for (int j = 0; j < 4; ++j) {
                    mma16816(st, qa[j].x, qb[j].x, qa[j].y, qb[j].y, kt[j].x, kt[j].y);
                    mma16816(st, qa[j].z, qb[j].z, qa[j].w, qb[j].w, kt[j].z, kt[j].w);
                }
                const float bias0 = (1.0f - __uint_as_float(mk << 16)) * (-1.0e9f * 1.4426950408889634f);
                const float bias1 = (1.0f - __uint_as_float(mk & 0xffff0000u)) * (-1.0e9f * 1.4426950408889634f);
                const float t0 = fmaf(st[0], c, bias0), t1 = fmaf(st[1], c, bias1);
                const float t2 = fmaf(st[2], c, bias0), t3 = fmaf(st[3], c, bias1);
                mt0 = quad_max(fmaxf(t0, t1));
                mt1 = quad_max(fmaxf(t2, t3));
                const uint32_t a0 = pack_bf16(ex2(t0 - mt0), ex2(t1 - mt0));
                const uint32_t a1 = pack_bf16(ex2(t2 - mt1), ex2(t3 - mt1));
#pragma unroll
                for (int n = 0; n < 2; ++n) {
                    acc[n][0] = 0.f; acc[n][1] = 0.f; acc[n][2] = 0.f; acc[n][3] = 0.f;
                    mma16816(acc[n], a0, a1, 0u, 0u, vt[n], 0u);
                }
                mma16816(lt, a0, a1, 0u, 0u, kOnes, 0u);
            }
            if (u + 1 < kPairsPerCta) fetch(u + 1);
            jitter(1);

            float w0[kG], w1[kG];
            mbar_wait_cluster(bar_ml + (u & 3) * 8, (u >> 2) & 1);
            {
                float4 ml[kG];
#pragma unroll
                for (int j = 0; j < kG; ++j)
                    ml[j] = *reinterpret_cast<const float4*>(sgen + kSmMl + (u & 3) * kMlBytes + j * 128 + g * 16);
                float M0 = mt0, M1 = mt1;
#pragma unroll
                for (int j = 0; j < kG; ++j) { M0 = fmaxf(M0, ml[j].x); M1 = fmaxf(M1, ml[j].z); }
                const float wt0 = ex2(mt0 - M0), wt1 = ex2(mt1 - M1);
                float L0 = lt[0] * wt0, L1 = lt[2] * wt1;
#pragma unroll
                for (int j = 0; j < kG; ++j) {
                    w0[j] = ex2(ml[j].x - M0);
                    w1[j] = ex2(ml[j].z - M1);
                    L0 = fmaf(ml[j].y, w0[j], L0);
                    L1 = fmaf(ml[j].w, w1[j], L1);
                }
                const float inv0 = 1.0f / L0, inv1 = 1.0f / L1;
#pragma unroll
                for (int j = 0; j < kG; ++j) { w0[j] *= inv0; w1[j] *= inv1; }
#pragma unroll
                for (int n = 0; n < 2; ++n) {
                    acc[n][0] *= wt0 * inv0; acc[n][1] *= wt0 * inv0;
                    acc[n][2] *= wt1 * inv1; acc[n][3] *= wt1 * inv1;
                }
            }
            __syncwarp();
            if (lane == 0) mbar_expect_tx(bar_ml + (u & 3) * 8, kMlBytes);
            jitter(2);

            mbar_wait_cluster(bar_rfull + s * 8, (u >> 1) & 1);
            const unsigned char* rb = sgen + kSmRecv + s * kRecvBytes;
#pragma unroll
            for (int j = 0; j < kG; ++j)
#pragma unroll
                for (int n = 0; n < 2; ++n) {
                    const float4 v = *reinterpret_cast<const float4*>(rb + ((j * 2 + n) * 32 + lane) * 16);
                    acc[n][0] = fmaf(v.x, w0[j], acc[n][0]); acc[n][1] = fmaf(v.y, w0[j], acc[n][1]);
                    acc[n][2] = fmaf(v.z, w1[j], acc[n][2]); acc[n][3] = fmaf(v.w, w1[j], acc[n][3]);
                }
            uint32_t* o0 = reinterpret_cast<uint32_t*>(out + ((size_t)pair * 16 + g) * kD + 16 * mem + 2 * tq);
#pragma unroll
            for (int n = 0; n < 2; ++n) {
                o0[4 * n] = pack_bf16(acc[n][0], acc[n][1]);
                o0[4 * n + 8 * kD / 2] = pack_bf16(acc[n][2], acc[n][3]);
            }
            jitter(6);
            __syncwarp();
            if (lane == 0) {
                mbar_expect_tx(bar_rfull + s * 8, kRecvBytes);
                mbar_arrive(bar_cdone + s * 8);
            }
        }
    } else {
        const int g = lane >> 2;
        const int tq = lane & 3;
        const int mi = lane >> 3;
        const int lr = lane & 7;

        const uint32_t k_row = (uint32_t)(16 * warp + 8 * (mi >> 1) + lr) * 128u;
        const uint32_t k_x = (uint32_t)(((mi & 1) ^ lr) << 4);
        const uint32_t q_row = (uint32_t)(8 * (mi & 1) + lr) * 128u;
        const uint32_t q_x = (uint32_t)(((mi >> 1) ^ lr) << 4);
        const uint32_t v_row = (uint32_t)(warp >> 1) * 8192u + (uint32_t)(8 * (mi & 1) + lr) * 128u;
        const uint32_t v_x0 = (uint32_t)(((4 * (warp & 1) + (mi >> 1)) ^ lr) << 4);
        const uint32_t v_x1 = v_x0 ^ 32u;

        uint4* const pbuf = reinterpret_cast<uint4*>(sgen + kSmP);
        float* const smax = reinterpret_cast<float*>(sgen + kSmMax);
        float* const ssum = reinterpret_cast<float*>(sgen + kSmSum);

        const uint32_t rem0 = mapa(sb, 2 * warp), rem1 = mapa(sb, 2 * warp + 1);
        const uint32_t rem_ml = (tq == 0 ? rem0 : rem1);

        int slot = 0;
        uint32_t phase = 0;

        auto release = [&](int sl) {
            __syncwarp();
            if (lane == 0) mbar_arrive(bar_empty + sl * 8);
        };
        auto load_k = [&](uint32_t (&f)[8][4], int sl) {
            const uint32_t base = sb + kSmRing + sl * kTileBytes + k_row;
#pragma unroll
            for (int ks = 0; ks < 8; ++ks)
                ldsm4(f[ks][0], f[ks][1], f[ks][2], f[ks][3], base + (ks >> 2) * 8192 + (k_x ^ ((ks & 3) << 5)));
        };
        auto load_v = [&](uint32_t (&f)[8][4], int sl) {
            const uint32_t base = sb + kSmRing + sl * kTileBytes + v_row;
#pragma unroll
            for (int ks = 0; ks < 4; ++ks) {
                ldsm4t(f[2 * ks][0], f[2 * ks][1], f[2 * ks][2], f[2 * ks][3], base + ks * 2048 + v_x0);
                ldsm4t(f[2 * ks + 1][0], f[2 * ks + 1][1], f[2 * ks + 1][2], f[2 * ks + 1][3], base + ks * 2048 + v_x1);
            }
        };

        for (int u = 0; u < kPairsPerCta; ++u) {
            mbar_wait(bar_q + (u & 1) * 8, (u >> 1) & 1);
            uint32_t qf[8][4];
            {
                const uint32_t qa = sb + kSmQ + (u & 1) * 4096 + q_row;
#pragma unroll
                for (int ks = 0; ks < 8; ++ks)
                    ldsm4(qf[ks][0], qf[ks][1], qf[ks][2], qf[ks][3], qa + (ks >> 2) * 2048 + (q_x ^ ((ks & 3) << 5)));
            }
            float s[kRun][2][4];
            auto qk = [&](const uint32_t (&f)[8][4], float (&d)[2][4]) {
                float h[2][4];
#pragma unroll
                for (int e = 0; e < 4; ++e) { d[0][e] = 0.f; d[1][e] = 0.f; h[0][e] = 0.f; h[1][e] = 0.f; }
#pragma unroll
                for (int ks = 0; ks < 8; ks += 2) {
                    mma16816(d[0], qf[ks][0], qf[ks][1], qf[ks][2], qf[ks][3], f[ks][0], f[ks][1]);
                    mma16816(d[1], qf[ks][0], qf[ks][1], qf[ks][2], qf[ks][3], f[ks][2], f[ks][3]);
                    mma16816(h[0], qf[ks + 1][0], qf[ks + 1][1], qf[ks + 1][2], qf[ks + 1][3], f[ks + 1][0], f[ks + 1][1]);
                    mma16816(h[1], qf[ks + 1][0], qf[ks + 1][1], qf[ks + 1][2], qf[ks + 1][3], f[ks + 1][2], f[ks + 1][3]);
                }
#pragma unroll
                for (int e = 0; e < 4; ++e) { d[0][e] += h[0][e]; d[1][e] += h[1][e]; }
            };
#pragma unroll
            for (int t = 0; t < kRun; t += 2) {
                uint32_t fa[8][4], fb[8][4];
                mbar_wait(bar_full + slot * 8, phase);
                const bool early = __all_sync(0xffffffffu, mbar_test(bar_full + slot * 8 + 8, phase));
                load_k(fa, slot);
                if (early) load_k(fb, slot + 1);
                qk(fa, s[t]);
                if (!early) {
                    release(slot);
                    mbar_wait(bar_full + slot * 8 + 8, phase);
                    load_k(fb, slot + 1);
                }
                qk(fb, s[t + 1]);
                if (early) release(slot);
                release(slot + 1);
                if ((slot += 2) == kNS) { slot = 0; phase ^= 1; }
            }
            jitter(3);
            float x0 = fmaxf(s[0][0][0], s[0][0][1]), x1 = fmaxf(s[0][0][2], s[0][0][3]);
#pragma unroll
            for (int t = 0; t < kRun; ++t)
#pragma unroll
                for (int n = 0; n < 2; ++n) {
                    x0 = fmaxf(x0, fmaxf(s[t][n][0], s[t][n][1]));
                    x1 = fmaxf(x1, fmaxf(s[t][n][2], s[t][n][3]));
                }
            x0 = quad_max(x0);
            x1 = quad_max(x1);
            if (tq == 0) {
                smax[g * kCW + warp] = x0;
                smax[(g + 8) * kCW + warp] = x1;
            }
            asm volatile("bar.sync 1, %0;" ::"n"(kCW * 32) : "memory");
            {
                const float4 a = *reinterpret_cast<const float4*>(smax + g * kCW);
                const float4 b = *reinterpret_cast<const float4*>(smax + (g + 8) * kCW);
                x0 = fmaxf(fmaxf(a.x, a.y), fmaxf(a.z, a.w));
                x1 = fmaxf(fmaxf(b.x, b.y), fmaxf(b.z, b.w));
            }
            const float m0 = x0 * c, m1 = x1 * c;
            float r0 = 0.f, r1 = 0.f;
#pragma unroll
            for (int t = 0; t < kRun; ++t) {
                uint32_t pf[4];
#pragma unroll
                for (int n = 0; n < 2; ++n) {
                    const float p0 = ex2(fmaf(s[t][n][0], c, -m0)), p1 = ex2(fmaf(s[t][n][1], c, -m0));
                    const float p2 = ex2(fmaf(s[t][n][2], c, -m1)), p3 = ex2(fmaf(s[t][n][3], c, -m1));
                    r0 += p0 + p1;
                    r1 += p2 + p3;
                    pf[2 * n] = pack_bf16(p0, p1);
                    pf[2 * n + 1] = pack_bf16(p2, p3);
                }
                pbuf[(t * kCW + warp) * 32 + lane] = make_uint4(pf[0], pf[1], pf[2], pf[3]);
            }
            r0 = quad_sum(r0);
            r1 = quad_sum(r1);
            if (tq == 0) {
                ssum[g * kCW + warp] = r0;
                ssum[(g + 8) * kCW + warp] = r1;
            }
            asm volatile("bar.sync 1, %0;" ::"n"(kCW * 32) : "memory");
            jitter(4);
            {
                const float4 a = *reinterpret_cast<const float4*>(ssum + g * kCW);
                const float4 b = *reinterpret_cast<const float4*>(ssum + (g + 8) * kCW);
                if (u == 0) asm volatile("barrier.cluster.wait.acquire.aligned;" ::: "memory");
                if (tq < 2)
                    st_async4(rem_ml + kSmMl + (u & 3) * kMlBytes + mem * 128 + g * 16, m0, (a.x + a.y) + (a.z + a.w), m1,
                              (b.x + b.y) + (b.z + b.w), rem_ml + kSmBar + (2 * kNS + 6 + (u & 3)) * 8);
            }
            float o[2][4][4];
#pragma unroll
            for (int n = 0; n < 8; ++n) { o[n >> 2][n & 3][0] = 0.f; o[n >> 2][n & 3][1] = 0.f; o[n >> 2][n & 3][2] = 0.f; o[n >> 2][n & 3][3] = 0.f; }
            auto pv = [&](const uint32_t (&f)[8][4], const uint4* pa) {
#pragma unroll
                for (int ks = 0; ks < 4; ++ks) {
                    const uint4 a = pa[ks];
                    mma16816(o[ks & 1][0], a.x, a.y, a.z, a.w, f[2 * ks][0], f[2 * ks][1]);
                    mma16816(o[ks & 1][1], a.x, a.y, a.z, a.w, f[2 * ks][2], f[2 * ks][3]);
                    mma16816(o[ks & 1][2], a.x, a.y, a.z, a.w, f[2 * ks + 1][0], f[2 * ks + 1][1]);
                    mma16816(o[ks & 1][3], a.x, a.y, a.z, a.w, f[2 * ks + 1][2], f[2 * ks + 1][3]);
                }
            };
#pragma unroll
            for (int t = 0; t < kRun; t += 2) {
                uint32_t fa[8][4], fb[8][4];
                uint4 pa[2 * kCW];
#pragma unroll
                for (int i = 0; i < 2 * kCW; ++i) pa[i] = pbuf[(t * kCW + i) * 32 + lane];
                if (t == kRun - 2 && u > 0) mbar_wait(bar_cdone + ((u - 1) & 1) * 8, ((u - 1) >> 1) & 1);
                mbar_wait(bar_full + slot * 8, phase);
                const bool early = __all_sync(0xffffffffu, mbar_test(bar_full + slot * 8 + 8, phase));
                load_v(fa, slot);
                if (early) load_v(fb, slot + 1);
                pv(fa, pa);
                if (!early) {
                    release(slot);
                    mbar_wait(bar_full + slot * 8 + 8, phase);
                    load_v(fb, slot + 1);
                }
                pv(fb, pa + kCW);
                if (early) release(slot);
                release(slot + 1);
                if ((slot += 2) == kNS) { slot = 0; phase ^= 1; }
            }
            jitter(5);
            {
                const uint32_t doff = kSmRecv + (u & 1) * kRecvBytes + (uint32_t)(mem * 64 + lane) * 16u;
                const uint32_t boff = kSmBar + (2 * kNS + 2 + (u & 1)) * 8;
#pragma unroll
                for (int n = 0; n < 4; ++n) {
                    const uint32_t rem = n < 2 ? rem0 : rem1;
                    st_async4(rem + doff + (n & 1) * 512, o[0][n][0] + o[1][n][0], o[0][n][1] + o[1][n][1],
                              o[0][n][2] + o[1][n][2], o[0][n][3] + o[1][n][3], rem + boff);
                }
            }
        }
    }
}

typedef CUresult (*EncodeTiledFn)(CUtensorMap*, CUtensorMapDataType, cuuint32_t, void*, const cuuint64_t*,
                                  const cuuint64_t*, const cuuint32_t*, const cuuint32_t*, CUtensorMapInterleave,
                                  CUtensorMapSwizzle, CUtensorMapL2promotion, CUtensorMapFloatOOBfill);

void make_map(EncodeTiledFn enc, CUtensorMap* tm, const void* base, int rows, int box_rows) {
    cuuint64_t dims[3] = {64, (cuuint64_t)rows, 2};
    cuuint64_t strides[2] = {256, 128};
    cuuint32_t box[3] = {64, (cuuint32_t)box_rows, 2};
    cuuint32_t es[3] = {1, 1, 1};
    enc(tm, CU_TENSOR_MAP_DATA_TYPE_BFLOAT16, 3, const_cast<void*>(base), dims, strides, box, es,
        CU_TENSOR_MAP_INTERLEAVE_NONE, CU_TENSOR_MAP_SWIZZLE_128B, CU_TENSOR_MAP_L2_PROMOTION_L2_256B,
        CU_TENSOR_MAP_FLOAT_OOB_FILL_NONE);
}

}

extern "C" void kernel_launch(void* const* d_in, const int* in_sizes, int n_in, void* d_out, int out_size) {
    (void)in_sizes; (void)n_in; (void)out_size;
    const __nv_bfloat16* q = (const __nv_bfloat16*)d_in[0];
    const void* k_cache = d_in[1];
    const void* v_cache = d_in[2];
    const __nv_bfloat16* k_tree = (const __nv_bfloat16*)d_in[3];
    const __nv_bfloat16* v_tree = (const __nv_bfloat16*)d_in[4];
    const __nv_bfloat16* mask = (const __nv_bfloat16*)d_in[5];

    static EncodeTiledFn enc = nullptr;
    if (!enc) {
        void* fn = nullptr;
        cudaDriverEntryPointQueryResult qr;
        cudaGetDriverEntryPoint("cuTensorMapEncodeTiled", &fn, cudaEnableDefault, &qr);
        enc = (EncodeTiledFn)fn;
        cudaFuncSetAttribute(tree_attn_kernel, cudaFuncAttributeMaxDynamicSharedMemorySize, kSmemBytes);
    }
    CUtensorMap tmK, tmV, tmQ;
    make_map(enc, &tmK, k_cache, kPairs * kC, kTileKeys);
    make_map(enc, &tmV, v_cache, kPairs * kC, kTileKeys);
    make_map(enc, &tmQ, q, kPairs * 16, 16);
    tree_attn_kernel<<<kGrid, kThreads, kSmemBytes>>>(tmK, tmV, tmQ, q, k_tree, v_tree, mask, (__nv_bfloat16*)d_out,
                                                      (const __nv_bfloat16*)k_cache, (const __nv_bfloat16*)v_cache);
}
```

```cpp
#include <cuda_runtime.h>
#include <cuda_bf16.h>
#include <cuda.h>
#include <stdint.h>

#define CFG_NS 8
#define CFG_F 5
#define CFG_FMIN 3
#define CFG_W 160
#define CFG_FMIN2 2
#define CFG_W2 260
#define CFG_ILV 2
#define CFG_SLEEP 200
#define CFG_PF 2
#define CFG_NC 16
#define CFG_JITTER 0

namespace {

constexpr int kB = 32, kHkv = 16, kT = 8, kC = 2048, kD = 128;
constexpr int kPairs = kB * kHkv;
constexpr int kG = 8;
constexpr int kTileKeys = 64;
constexpr int kTileBytes = kTileKeys * kD * 2;
constexpr int kRun = kC / kG / kTileKeys;
constexpr int kNS = CFG_NS;
constexpr int kF = CFG_F, kFM = CFG_FMIN, kFM2 = CFG_FMIN2;
constexpr int kCW = 4;
constexpr int kWIssue = 4, kWPoll = 5, kWComb = 6;
constexpr int kThreads = 224;
static_assert(kNS % 2 == 0 && kNS <= 16 && kF < kNS && kF <= 8 && kFM <= kF && kFM2 <= kFM && kFM2 >= 1, "config");

constexpr int kRecvBytes = kG * 1024;
constexpr int kMlBytes = kG * 128;

constexpr int kSmRing = 0;
constexpr int kSmQ = kSmRing + kNS * kTileBytes;
constexpr int kSmP = kSmQ + 2 * 4096;
constexpr int kSmRecv = kSmP + kRun * kCW * 32 * 16;
constexpr int kSmMl = kSmRecv + 2 * kRecvBytes;
constexpr int kSmMax = kSmMl + 4 * kMlBytes;
constexpr int kSmSum = kSmMax + 16 * kCW * 4;
constexpr int kSmBar = kSmSum + 16 * kCW * 4;
constexpr int kNumBars = 2 * kNS + 2 + 2 + 2 + 4;
constexpr int kSmPace = kSmBar + kNumBars * 8;
constexpr int kSmemBytes = kSmPace + 16 > 120 * 1024 ? kSmPace + 16 : 120 * 1024;
static_assert(kSmemBytes <= 232448, "shared memory");

__device__ __forceinline__ uint32_t smem_u32(const void* p) {
    return (uint32_t)__cvta_generic_to_shared(p);
}
__device__ __forceinline__ void mbar_init(uint32_t bar, int cnt) {
    asm volatile("mbarrier.init.shared::cta.b64 [%0], %1;" ::"r"(bar), "r"(cnt) : "memory");
}
__device__ __forceinline__ void mbar_expect_tx(uint32_t bar, uint32_t bytes) {
    asm volatile("mbarrier.arrive.expect_tx.shared::cta.b64 _, [%0], %1;" ::"r"(bar), "r"(bytes) : "memory");
}
__device__ __forceinline__ void mbar_arrive(uint32_t bar) {
    asm volatile("mbarrier.arrive.shared::cta.b64 _, [%0];" ::"r"(bar) : "memory");
}
__device__ __forceinline__ bool mbar_try(uint32_t bar, uint32_t parity) {
    uint32_t ok;
    asm volatile(
        "{\n.reg .pred p;\n"
        "mbarrier.try_wait.parity.shared::cta.b64 p, [%1], %2;\n"
        "selp.u32 %0, 1, 0, p;\n}"
        : "=r"(ok) : "r"(bar), "r"(parity) : "memory");
    return ok != 0;
}
__device__ __forceinline__ bool mbar_try_cluster(uint32_t bar, uint32_t parity) {
    uint32_t ok;
    asm volatile(
        "{\n.reg .pred p;\n"
        "mbarrier.try_wait.parity.acquire.cluster.shared::cta.b64 p, [%1], %2;\n"
        "selp.u32 %0, 1, 0, p;\n}"
        : "=r"(ok) : "r"(bar), "r"(parity) : "memory");
    return ok != 0;
}
__device__ __forceinline__ bool mbar_test(uint32_t bar, uint32_t parity) {
    uint32_t ok;
    asm volatile(
        "{\n.reg .pred p;\n"
        "mbarrier.test_wait.parity.shared::cta.b64 p, [%1], %2;\n"
        "selp.u32 %0, 1, 0, p;\n}"
        : "=r"(ok) : "r"(bar), "r"(parity) : "memory");
    return ok != 0;
}
__device__ __forceinline__ void mbar_wait(uint32_t bar, uint32_t parity) {
    for (uint32_t it = 0; !mbar_try(bar, parity); ++it)
        if (it > (1u << 22)) __trap();
}
__device__ __forceinline__ void mbar_wait_cluster(uint32_t bar, uint32_t parity) {
    for (uint32_t it = 0; !mbar_try_cluster(bar, parity); ++it)
        if (it > (1u << 22)) __trap();
}
__device__ __forceinline__ uint32_t lds_volatile(uint32_t a) {
    uint32_t v;
    asm volatile("ld.volatile.shared.u32 %0, [%1];" : "=r"(v) : "r"(a) : "memory");
    return v;
}
__device__ __forceinline__ void sts_volatile(uint32_t a, uint32_t v) {
    asm volatile("st.volatile.shared.u32 [%0], %1;" ::"r"(a), "r"(v) : "memory");
}
__device__ __forceinline__ uint32_t mapa(uint32_t addr, uint32_t rank) {
    uint32_t r;
    asm("mapa.shared::cluster.u32 %0, %1, %2;" : "=r"(r) : "r"(addr), "r"(rank));
    return r;
}
__device__ __forceinline__ void st_async4(uint32_t addr, float a, float b, float c, float d, uint32_t bar) {
    asm volatile("st.async.weak.shared::cluster.mbarrier::complete_tx::bytes.v4.f32 [%0], {%1,%2,%3,%4}, [%5];"
                 ::"r"(addr), "f"(a), "f"(b), "f"(c), "f"(d), "r"(bar) : "memory");
}
__device__ __forceinline__ void tma_tile(uint32_t dst, const CUtensorMap* tm, int row, uint32_t bar, uint64_t pol) {
    asm volatile(
        "cp.async.bulk.tensor.3d.shared::cluster.global.mbarrier::complete_tx::bytes.L2::cache_hint "
        "[%0], [%1, {%3, %4, %5}], [%2], %6;"
        ::"r"(dst), "l"(tm), "r"(bar), "r"(0), "r"(row), "r"(0), "l"(pol) : "memory");
}
__device__ __forceinline__ void tma_tile_nohint(uint32_t dst, const CUtensorMap* tm, int row, uint32_t bar) {
    asm volatile(
        "cp.async.bulk.tensor.3d.shared::cluster.global.mbarrier::complete_tx::bytes "
        "[%0], [%1, {%3, %4, %5}], [%2];"
        ::"r"(dst), "l"(tm), "r"(bar), "r"(0), "r"(row), "r"(0) : "memory");
}
__device__ __forceinline__ void ldsm4(uint32_t& r0, uint32_t& r1, uint32_t& r2, uint32_t& r3, uint32_t addr) {
    asm volatile("ldmatrix.sync.aligned.m8n8.x4.shared.b16 {%0,%1,%2,%3}, [%4];"
                 : "=r"(r0), "=r"(r1), "=r"(r2), "=r"(r3) : "r"(addr) : "memory");
}
__device__ __forceinline__ void ldsm4t(uint32_t& r0, uint32_t& r1, uint32_t& r2, uint32_t& r3, uint32_t addr) {
    asm volatile("ldmatrix.sync.aligned.m8n8.x4.trans.shared.b16 {%0,%1,%2,%3}, [%4];"
                 : "=r"(r0), "=r"(r1), "=r"(r2), "=r"(r3) : "r"(addr) : "memory");
}
__device__ __forceinline__ void mma16816(float (&c)[4], uint32_t a0, uint32_t a1, uint32_t a2, uint32_t a3,
                                         uint32_t b0, uint32_t b1) {
    asm("mma.sync.aligned.m16n8k16.row.col.f32.bf16.bf16.f32 {%0,%1,%2,%3}, {%4,%5,%6,%7}, {%8,%9}, {%0,%1,%2,%3};"
        : "+f"(c[0]), "+f"(c[1]), "+f"(c[2]), "+f"(c[3])
        : "r"(a0), "r"(a1), "r"(a2), "r"(a3), "r"(b0), "r"(b1));
}
__device__ __forceinline__ float ex2(float x) {
    float y;
    asm("ex2.approx.ftz.f32 %0, %1;" : "=f"(y) : "f"(x));
    return y;
}
__device__ __forceinline__ uint32_t pack_bf16(float lo, float hi) {
    uint32_t r;
    asm("cvt.rn.bf16x2.f32 %0, %1, %2;" : "=r"(r) : "f"(hi), "f"(lo));
    return r;
}
__device__ __forceinline__ float quad_max(float v) {
    v = fmaxf(v, __shfl_xor_sync(0xffffffffu, v, 1));
    v = fmaxf(v, __shfl_xor_sync(0xffffffffu, v, 2));
    return v;
}
__device__ __forceinline__ float quad_sum(float v) {
    v += __shfl_xor_sync(0xffffffffu, v, 1);
    v += __shfl_xor_sync(0xffffffffu, v, 2);
    return v;
}
__device__ __forceinline__ void jitter(uint32_t salt) {
    (void)salt;
}

__device__ __forceinline__ int tile_pos(int t, int mem) {
    return CFG_ILV == 0 ? t * kG + mem : CFG_ILV == 1 ? ((t >> 1) * kG + mem) * 2 + (t & 1) : mem * kRun + t;
}

constexpr uint32_t kOnes = 0x3f803f80u;

__device__ unsigned g_progress;

__global__ void __cluster_dims__(kG, 1, 1) __launch_bounds__(kThreads, 1)
tree_attn_kernel(const __grid_constant__ CUtensorMap tmK, const __grid_constant__ CUtensorMap tmV,
                 const __grid_constant__ CUtensorMap tmQ, const __nv_bfloat16* __restrict__ q,
                 const __nv_bfloat16* __restrict__ k_tree, const __nv_bfloat16* __restrict__ v_tree,
                 const __nv_bfloat16* __restrict__ mask, __nv_bfloat16* __restrict__ out,
                 const __nv_bfloat16* __restrict__ kc) {
    if (threadIdx.x < CFG_PF) {
        const int key = (blockIdx.x / kG) * kC + tile_pos(threadIdx.x, blockIdx.x % kG) * kTileKeys;
        uint64_t p;
        asm volatile("createpolicy.fractional.L2::evict_first.b64 %0, 1.0;" : "=l"(p));
        asm volatile("cp.async.bulk.prefetch.L2.global.L2::cache_hint [%0], %1, %2;"
                     ::"l"(kc + (size_t)key * kD), "r"(kTileBytes), "l"(p) : "memory");
    }
    extern __shared__ __align__(1024) unsigned char sgen[];
    const uint32_t sb = smem_u32(sgen);

    const uint32_t bar_full = sb + kSmBar;
    const uint32_t bar_empty = bar_full + kNS * 8;
    const uint32_t bar_q = bar_empty + kNS * 8;
    const uint32_t bar_rfull = bar_q + 2 * 8;
    const uint32_t bar_cdone = bar_rfull + 2 * 8;
    const uint32_t bar_ml = bar_cdone + 2 * 8;
    const uint32_t s_total = sb + kSmPace, s_stop = s_total + 4;

    const int warp = threadIdx.x >> 5;
    const int lane = threadIdx.x & 31;
    const int cl = blockIdx.x / kG;
    const int mem = blockIdx.x % kG;
    const int nclusters = gridDim.x / kG;
    const int npairs = (kPairs - cl + nclusters - 1) / nclusters;
    const float c = 0.08838834764831845f * 1.4426950408889634f;

    uint64_t pol = 0;
    auto issue = [&](int j, int slot) {
        const int u = j >> 3;
        const int r = j & 7;
        const int pair = cl + u * nclusters;
        const int t = r & 3;
        const int key = pair * kC + tile_pos(t, mem) * kTileKeys;
        const uint32_t fb = bar_full + slot * 8;
        mbar_expect_tx(fb, kTileBytes);
        tma_tile(sb + kSmRing + slot * kTileBytes, r >= 4 ? &tmV : &tmK, key, fb, pol);
        if (r == 0) {
            const uint32_t qb = bar_q + (u & 1) * 8;
            mbar_expect_tx(qb, 4096);
            tma_tile_nohint(sb + kSmQ + (u & 1) * 4096, &tmQ, pair * 16, qb);
        }
    };

    asm volatile("createpolicy.fractional.L2::evict_first.b64 %0, 1.0;" : "=l"(pol));
    if (threadIdx.x == kWIssue * 32) {
#pragma unroll
        for (int i = 0; i < kF; ++i) mbar_init(bar_full + i * 8, 1);
        mbar_init(bar_q, 1);
        asm volatile("fence.proxy.async.shared::cta;" ::: "memory");
#pragma unroll
        for (int i = 0; i < kF; ++i) issue(i, i);
        for (int s = kF; s < kNS; ++s) mbar_init(bar_full + s * 8, 1);
        for (int s = 0; s < kNS; ++s) mbar_init(bar_empty + s * 8, kCW);
        mbar_init(bar_q + 8, 1);
        for (int s = 0; s < 2; ++s) {
            mbar_init(bar_cdone + s * 8, 1);
            mbar_init(bar_rfull + s * 8, 1);
            mbar_expect_tx(bar_rfull + s * 8, kRecvBytes);
        }
        for (int s = 0; s < 4; ++s) {
            mbar_init(bar_ml + s * 8, 1);
            mbar_expect_tx(bar_ml + s * 8, kMlBytes);
        }
        sts_volatile(s_total, 0);
        sts_volatile(s_stop, 0);
        asm volatile("fence.mbarrier_init.release.cluster;" ::: "memory");
        asm volatile("fence.proxy.async.shared::cta;" ::: "memory");
        if (sb & 1023u) __trap();
    }
    __syncthreads();
    asm volatile("barrier.cluster.arrive.relaxed.aligned;" ::: "memory");

    if (warp == kWIssue) {
        if (lane == 0) {
            int si = kF; uint32_t pe = 1;
            int sf = 0; uint32_t pf = 0;
            int sm = kF - kFM; uint32_t pm = 0;
            int sn = kF - kFM2; uint32_t pn = 0;
            const int ntiles = npairs * 2 * kRun;
            const int total = kG * (2 * kRun * kPairs - nclusters * kF);
            const float scale = (float)total / (float)(ntiles - kF);
            for (int j = kF; j < ntiles; ++j) {
                mbar_wait(bar_full + sf * 8, pf);
                if (++sf == kNS) { sf = 0; pf ^= 1; }
                asm volatile("red.relaxed.gpu.global.inc.u32 [%0], %1;"
                             ::"l"(&g_progress), "r"((unsigned)(total - 1)) : "memory");
                const int mine = (int)((float)(j - kF + 1) * scale) - CFG_W;
                for (uint32_t it = 0; mine > (int)lds_volatile(s_total) && !mbar_test(bar_full + sm * 8, pm); ++it)
                    if (it > (1u << 26)) __trap();
                if (++sm == kNS) { sm = 0; pm ^= 1; }
                for (uint32_t it = 0;
                     mine - (CFG_W2 - CFG_W) > (int)lds_volatile(s_total) && !mbar_test(bar_full + sn * 8, pn); ++it)
                    if (it > (1u << 26)) __trap();
                if (++sn == kNS) { sn = 0; pn ^= 1; }
                mbar_wait(bar_empty + si * 8, pe);
                issue(j, si);
                if (++si == kNS) { si = 0; pe ^= 1; }
            }
            sts_volatile(s_stop, 1);
        }
    } else if (warp == kWPoll) {
        if (lane == 0) {
            for (uint32_t it = 0; lds_volatile(s_stop) == 0 && it < (1u << 24); ++it) {
                unsigned t;
                asm volatile("ld.relaxed.gpu.global.u32 %0, [%1];" : "=r"(t) : "l"(&g_progress) : "memory");
                sts_volatile(s_total, t);
                __nanosleep(CFG_SLEEP);
            }
        }
    } else if (warp == kWComb) {
        const int g = lane >> 2, tq = lane & 3;
        uint4 qa[4], qb[4], kt[4];
        uint32_t vt[2], mk;
        auto fetch = [&](int u) {
            const int pair = cl + u * nclusters;
            const uint4* qp = reinterpret_cast<const uint4*>(q + ((size_t)pair * 16 + g) * kD) + tq;
            const uint4* kp = reinterpret_cast<const uint4*>(k_tree + ((size_t)pair * kT + g) * kD) + tq;
#pragma unroll
            for (int j = 0; j < 4; ++j) {
                qa[j] = __ldg(qp + 4 * j);
                qb[j] = __ldg(qp + 4 * j + 8 * kD / 8);
                kt[j] = __ldg(kp + 4 * j);
            }
            const unsigned short* vp =
                reinterpret_cast<const unsigned short*>(v_tree) + ((size_t)pair * kT + 2 * tq) * kD + 16 * mem + g;
#pragma unroll
            for (int n = 0; n < 2; ++n)
                vt[n] = (uint32_t)__ldg(vp + 8 * n) | ((uint32_t)__ldg(vp + 8 * n + kD) << 16);
            mk = __ldg(reinterpret_cast<const uint32_t*>(mask + (size_t)(pair / kHkv) * kT * kT + g * kT + 2 * tq));
        };
        fetch(0);
        for (int u = 0; u < npairs; ++u) {
            const int s = u & 1;
            const int pair = cl + u * nclusters;
            float acc[2][4], lt[4] = {0.f, 0.f, 0.f, 0.f}, mt0, mt1;
            {
                float st[4] = {0.f, 0.f, 0.f, 0.f};
#pragma unroll
                for (int j = 0; j < 4; ++j) {
                    mma16816(st, qa[j].x, qb[j].x, qa[j].y, qb[j].y, kt[j].x, kt[j].y);
                    mma16816(st, qa[j].z, qb[j].z, qa[j].w, qb[j].w, kt[j].z, kt[j].w);
                }
                const float bias0 = (1.0f - __uint_as_float(mk << 16)) * (-1.0e9f * 1.4426950408889634f);
                const float bias1 = (1.0f - __uint_as_float(mk & 0xffff0000u)) * (-1.0e9f * 1.4426950408889634f);
                const float t0 = fmaf(st[0], c, bias0), t1 = fmaf(st[1], c, bias1);
                const float t2 = fmaf(st[2], c, bias0), t3 = fmaf(st[3], c, bias1);
                mt0 = quad_max(fmaxf(t0, t1));
                mt1 = quad_max(fmaxf(t2, t3));
                const uint32_t a0 = pack_bf16(ex2(t0 - mt0), ex2(t1 - mt0));
                const uint32_t a1 = pack_bf16(ex2(t2 - mt1), ex2(t3 - mt1));
#pragma unroll
                for (int n = 0; n < 2; ++n) {
                    acc[n][0] = 0.f; acc[n][1] = 0.f; acc[n][2] = 0.f; acc[n][3] = 0.f;
                    mma16816(acc[n], a0, a1, 0u, 0u, vt[n], 0u);
                }
                mma16816(lt, a0, a1, 0u, 0u, kOnes, 0u);
            }
            if (u + 1 < npairs) fetch(u + 1);
            jitter(1);

            float w0[kG], w1[kG];
            mbar_wait_cluster(bar_ml + (u & 3) * 8, (u >> 2) & 1);
            {
                float4 ml[kG];
#pragma unroll
                for (int j = 0; j < kG; ++j)
                    ml[j] = *reinterpret_cast<const float4*>(sgen + kSmMl + (u & 3) * kMlBytes + j * 128 + g * 16);
                float M0 = mt0, M1 = mt1;
#pragma unroll
                for (int j = 0; j < kG; ++j) { M0 = fmaxf(M0, ml[j].x); M1 = fmaxf(M1, ml[j].z); }
                const float wt0 = ex2(mt0 - M0), wt1 = ex2(mt1 - M1);
                float L0 = lt[0] * wt0, L1 = lt[2] * wt1;
#pragma unroll
                for (int j = 0; j < kG; ++j) {
                    w0[j] = ex2(ml[j].x - M0);
                    w1[j] = ex2(ml[j].z - M1);
                    L0 = fmaf(ml[j].y, w0[j], L0);
                    L1 = fmaf(ml[j].w, w1[j], L1);
                }
                const float inv0 = 1.0f / L0, inv1 = 1.0f / L1;
#pragma unroll
                for (int j = 0; j < kG; ++j) { w0[j] *= inv0; w1[j] *= inv1; }
#pragma unroll
                for (int n = 0; n < 2; ++n) {
                    acc[n][0] *= wt0 * inv0; acc[n][1] *= wt0 * inv0;
                    acc[n][2] *= wt1 * inv1; acc[n][3] *= wt1 * inv1;
                }
            }
            __syncwarp();
            if (lane == 0) mbar_expect_tx(bar_ml + (u & 3) * 8, kMlBytes);
            jitter(2);

            mbar_wait_cluster(bar_rfull + s * 8, (u >> 1) & 1);
            const unsigned char* rb = sgen + kSmRecv + s * kRecvBytes;
#pragma unroll
            for (int j = 0; j < kG; ++j)
#pragma unroll
                for (int n = 0; n < 2; ++n) {
                    const float4 v = *reinterpret_cast<const float4*>(rb + ((j * 2 + n) * 32 + lane) * 16);
                    acc[n][0] = fmaf(v.x, w0[j], acc[n][0]); acc[n][1] = fmaf(v.y, w0[j], acc[n][1]);
                    acc[n][2] = fmaf(v.z, w1[j], acc[n][2]); acc[n][3] = fmaf(v.w, w1[j], acc[n][3]);
                }
            uint32_t* o0 = reinterpret_cast<uint32_t*>(out + ((size_t)pair * 16 + g) * kD + 16 * mem + 2 * tq);
#pragma unroll
            for (int n = 0; n < 2; ++n) {
                o0[4 * n] = pack_bf16(acc[n][0], acc[n][1]);
                o0[4 * n + 8 * kD / 2] = pack_bf16(acc[n][2], acc[n][3]);
            }
            jitter(6);
            __syncwarp();
            if (lane == 0) {
                mbar_expect_tx(bar_rfull + s * 8, kRecvBytes);
                mbar_arrive(bar_cdone + s * 8);
            }
        }
    } else {
        const int g = lane >> 2;
        const int tq = lane & 3;
        const int mi = lane >> 3;
        const int lr = lane & 7;

        const uint32_t k_row = (uint32_t)(16 * warp + 8 * (mi >> 1) + lr) * 128u;
        const uint32_t k_x = (uint32_t)(((mi & 1) ^ lr) << 4);
        const uint32_t q_row = (uint32_t)(8 * (mi & 1) + lr) * 128u;
        const uint32_t q_x = (uint32_t)(((mi >> 1) ^ lr) << 4);
        const uint32_t v_row = (uint32_t)(warp >> 1) * 8192u + (uint32_t)(8 * (mi & 1) + lr) * 128u;
        const uint32_t v_x0 = (uint32_t)(((4 * (warp & 1) + (mi >> 1)) ^ lr) << 4);
        const uint32_t v_x1 = v_x0 ^ 32u;

        uint4* const pbuf = reinterpret_cast<uint4*>(sgen + kSmP);
        float* const smax = reinterpret_cast<float*>(sgen + kSmMax);
        float* const ssum = reinterpret_cast<float*>(sgen + kSmSum);

        const uint32_t rem0 = mapa(sb, 2 * warp), rem1 = mapa(sb, 2 * warp + 1);
        const uint32_t rem_ml = (tq == 0 ? rem0 : rem1);

        int slot = 0;
        uint32_t phase = 0;

        auto release = [&](int sl) {
            __syncwarp();
            if (lane == 0) mbar_arrive(bar_empty + sl * 8);
        };
        auto load_k = [&](uint32_t (&f)[8][4], int sl) {
            const uint32_t base = sb + kSmRing + sl * kTileBytes + k_row;
#pragma unroll
            for (int ks = 0; ks < 8; ++ks)
                ldsm4(f[ks][0], f[ks][1], f[ks][2], f[ks][3], base + (ks >> 2) * 8192 + (k_x ^ ((ks & 3) << 5)));
        };
        auto load_v = [&](uint32_t (&f)[8][4], int sl) {
            const uint32_t base = sb + kSmRing + sl * kTileBytes + v_row;
#pragma unroll
            for (int ks = 0; ks < 4; ++ks) {
                ldsm4t(f[2 * ks][0], f[2 * ks][1], f[2 * ks][2], f[2 * ks][3], base + ks * 2048 + v_x0);
                ldsm4t(f[2 * ks + 1][0], f[2 * ks + 1][1], f[2 * ks + 1][2], f[2 * ks + 1][3], base + ks * 2048 + v_x1);
            }
        };

        for (int u = 0; u < npairs; ++u) {
            mbar_wait(bar_q + (u & 1) * 8, (u >> 1) & 1);
            uint32_t qf[8][4];
            {
                const uint32_t qa = sb + kSmQ + (u & 1) * 4096 + q_row;
#pragma unroll
                for (int ks = 0; ks < 8; ++ks)
                    ldsm4(qf[ks][0], qf[ks][1], qf[ks][2], qf[ks][3], qa + (ks >> 2) * 2048 + (q_x ^ ((ks & 3) << 5)));
            }
            float s[kRun][2][4];
            auto qk = [&](const uint32_t (&f)[8][4], float (&d)[2][4]) {
                float h[2][4];
#pragma unroll
                for (int e = 0; e < 4; ++e) { d[0][e] = 0.f; d[1][e] = 0.f; h[0][e] = 0.f; h[1][e] = 0.f; }
#pragma unroll
                for (int ks = 0; ks < 8; ks += 2) {
                    mma16816(d[0], qf[ks][0], qf[ks][1], qf[ks][2], qf[ks][3], f[ks][0], f[ks][1]);
                    mma16816(d[1], qf[ks][0], qf[ks][1], qf[ks][2], qf[ks][3], f[ks][2], f[ks][3]);
                    mma16816(h[0], qf[ks + 1][0], qf[ks + 1][1], qf[ks + 1][2], qf[ks + 1][3], f[ks + 1][0], f[ks + 1][1]);
                    mma16816(h[1], qf[ks + 1][0], qf[ks + 1][1], qf[ks + 1][2], qf[ks + 1][3], f[ks + 1][2], f[ks + 1][3]);
                }
#pragma unroll
                for (int e = 0; e < 4; ++e) { d[0][e] += h[0][e]; d[1][e] += h[1][e]; }
            };
#pragma unroll
            for (int t = 0; t < kRun; t += 2) {
                uint32_t fa[8][4], fb[8][4];
                mbar_wait(bar_full + slot * 8, phase);
                const bool early = __all_sync(0xffffffffu, mbar_test(bar_full + slot * 8 + 8, phase));
                load_k(fa, slot);
                if (early) load_k(fb, slot + 1);
                qk(fa, s[t]);
                if (!early) {
                    release(slot);
                    mbar_wait(bar_full + slot * 8 + 8, phase);
                    load_k(fb, slot + 1);
                }
                qk(fb, s[t + 1]);
                if (early) release(slot);
                release(slot + 1);
                if ((slot += 2) == kNS) { slot = 0; phase ^= 1; }
            }
            jitter(3);
            float x0 = fmaxf(s[0][0][0], s[0][0][1]), x1 = fmaxf(s[0][0][2], s[0][0][3]);
#pragma unroll
            for (int t = 0; t < kRun; ++t)
#pragma unroll
                for (int n = 0; n < 2; ++n) {
                    x0 = fmaxf(x0, fmaxf(s[t][n][0], s[t][n][1]));
                    x1 = fmaxf(x1, fmaxf(s[t][n][2], s[t][n][3]));
                }
            x0 = quad_max(x0);
            x1 = quad_max(x1);
            if (tq == 0) {
                smax[g * kCW + warp] = x0;
                smax[(g + 8) * kCW + warp] = x1;
            }
            asm volatile("bar.sync 1, %0;" ::"n"(kCW * 32) : "memory");
            {
                const float4 a = *reinterpret_cast<const float4*>(smax + g * kCW);
                const float4 b = *reinterpret_cast<const float4*>(smax + (g + 8) * kCW);
                x0 = fmaxf(fmaxf(a.x, a.y), fmaxf(a.z, a.w));
                x1 = fmaxf(fmaxf(b.x, b.y), fmaxf(b.z, b.w));
            }
            const float m0 = x0 * c, m1 = x1 * c;
            float r0 = 0.f, r1 = 0.f;
#pragma unroll
            for (int t = 0; t < kRun; ++t) {
                uint32_t pf[4];
#pragma unroll
                for (int n = 0; n < 2; ++n) {
                    const float p0 = ex2(fmaf(s[t][n][0], c, -m0)), p1 = ex2(fmaf(s[t][n][1], c, -m0));
                    const float p2 = ex2(fmaf(s[t][n][2], c, -m1)), p3 = ex2(fmaf(s[t][n][3], c, -m1));
                    r0 += p0 + p1;
                    r1 += p2 + p3;
                    pf[2 * n] = pack_bf16(p0, p1);
                    pf[2 * n + 1] = pack_bf16(p2, p3);
                }
                pbuf[(t * kCW + warp) * 32 + lane] = make_uint4(pf[0], pf[1], pf[2], pf[3]);
            }
            r0 = quad_sum(r0);
            r1 = quad_sum(r1);
            if (tq == 0) {
                ssum[g * kCW + warp] = r0;
                ssum[(g + 8) * kCW + warp] = r1;
            }
            asm volatile("bar.sync 1, %0;" ::"n"(kCW * 32) : "memory");
            jitter(4);
            {
                const float4 a = *reinterpret_cast<const float4*>(ssum + g * kCW);
                const float4 b = *reinterpret_cast<const float4*>(ssum + (g + 8) * kCW);
                if (u == 0) asm volatile("barrier.cluster.wait.acquire.aligned;" ::: "memory");
                if (tq < 2)
                    st_async4(rem_ml + kSmMl + (u & 3) * kMlBytes + mem * 128 + g * 16, m0, (a.x + a.y) + (a.z + a.w), m1,
                              (b.x + b.y) + (b.z + b.w), rem_ml + kSmBar + (2 * kNS + 6 + (u & 3)) * 8);
            }
            float o[2][4][4];
#pragma unroll
            for (int n = 0; n < 8; ++n) { o[n >> 2][n & 3][0] = 0.f; o[n >> 2][n & 3][1] = 0.f; o[n >> 2][n & 3][2] = 0.f; o[n >> 2][n & 3][3] = 0.f; }
            auto pv = [&](const uint32_t (&f)[8][4], const uint4* pa) {
#pragma unroll
                for (int ks = 0; ks < 4; ++ks) {
                    const uint4 a = pa[ks];
                    mma16816(o[ks & 1][0], a.x, a.y, a.z, a.w, f[2 * ks][0], f[2 * ks][1]);
                    mma16816(o[ks & 1][1], a.x, a.y, a.z, a.w, f[2 * ks][2], f[2 * ks][3]);
                    mma16816(o[ks & 1][2], a.x, a.y, a.z, a.w, f[2 * ks + 1][0], f[2 * ks + 1][1]);
                    mma16816(o[ks & 1][3], a.x, a.y, a.z, a.w, f[2 * ks + 1][2], f[2 * ks + 1][3]);
                }
            };
#pragma unroll
            for (int t = 0; t < kRun; t += 2) {
                uint32_t fa[8][4], fb[8][4];
                uint4 pa[2 * kCW];
#pragma unroll
                for (int i = 0; i < 2 * kCW; ++i) pa[i] = pbuf[(t * kCW + i) * 32 + lane];
                if (t == kRun - 2 && u > 0) mbar_wait(bar_cdone + ((u - 1) & 1) * 8, ((u - 1) >> 1) & 1);
                mbar_wait(bar_full + slot * 8, phase);
                const bool early = __all_sync(0xffffffffu, mbar_test(bar_full + slot * 8 + 8, phase));
                load_v(fa, slot);
                if (early) load_v(fb, slot + 1);
                pv(fa, pa);
                if (!early) {
                    release(slot);
                    mbar_wait(bar_full + slot * 8 + 8, phase);
                    load_v(fb, slot + 1);
                }
                pv(fb, pa + kCW);
                if (early) release(slot);
                release(slot + 1);
                if ((slot += 2) == kNS) { slot = 0; phase ^= 1; }
            }
            jitter(5);
            {
                const uint32_t doff = kSmRecv + (u & 1) * kRecvBytes + (uint32_t)(mem * 64 + lane) * 16u;
                const uint32_t boff = kSmBar + (2 * kNS + 2 + (u & 1)) * 8;
#pragma unroll
                for (int n = 0; n < 4; ++n) {
                    const uint32_t rem = n < 2 ? rem0 : rem1;
                    st_async4(rem + doff + (n & 1) * 512, o[0][n][0] + o[1][n][0], o[0][n][1] + o[1][n][1],
                              o[0][n][2] + o[1][n][2], o[0][n][3] + o[1][n][3], rem + boff);
                }
            }
        }
    }
}

typedef CUresult (*EncodeTiledFn)(CUtensorMap*, CUtensorMapDataType, cuuint32_t, void*, const cuuint64_t*,
                                  const cuuint64_t*, const cuuint32_t*, const cuuint32_t*, CUtensorMapInterleave,
                                  CUtensorMapSwizzle, CUtensorMapL2promotion, CUtensorMapFloatOOBfill);

void make_map(EncodeTiledFn enc, CUtensorMap* tm, const void* base, int rows, int box_rows) {
    cuuint64_t dims[3] = {64, (cuuint64_t)rows, 2};
    cuuint64_t strides[2] = {256, 128};
    cuuint32_t box[3] = {64, (cuuint32_t)box_rows, 2};
    cuuint32_t es[3] = {1, 1, 1};
    enc(tm, CU_TENSOR_MAP_DATA_TYPE_BFLOAT16, 3, const_cast<void*>(base), dims, strides, box, es,
        CU_TENSOR_MAP_INTERLEAVE_NONE, CU_TENSOR_MAP_SWIZZLE_128B, CU_TENSOR_MAP_L2_PROMOTION_L2_256B,
        CU_TENSOR_MAP_FLOAT_OOB_FILL_NONE);
}

}

extern "C" void kernel_launch(void* const* d_in, const int* in_sizes, int n_in, void* d_out, int out_size) {
    (void)in_sizes; (void)n_in; (void)out_size;
    const __nv_bfloat16* q = (const __nv_bfloat16*)d_in[0];
    const void* k_cache = d_in[1];
    const void* v_cache = d_in[2];
    const __nv_bfloat16* k_tree = (const __nv_bfloat16*)d_in[3];
    const __nv_bfloat16* v_tree = (const __nv_bfloat16*)d_in[4];
    const __nv_bfloat16* mask = (const __nv_bfloat16*)d_in[5];

    static EncodeTiledFn enc = nullptr;
    static int nclusters = 0;
    if (!enc) {
        void* fn = nullptr;
        cudaDriverEntryPointQueryResult qr;
        cudaGetDriverEntryPoint("cuTensorMapEncodeTiled", &fn, cudaEnableDefault, &qr);
        enc = (EncodeTiledFn)fn;
        cudaFuncSetAttribute(tree_attn_kernel, cudaFuncAttributeMaxDynamicSharedMemorySize, kSmemBytes);
        cudaLaunchConfig_t cfg = {};
        cfg.gridDim = dim3(kG * CFG_NC);
        cfg.blockDim = dim3(kThreads);
        cfg.dynamicSmemBytes = kSmemBytes;
        cudaLaunchAttribute at;
        at.id = cudaLaunchAttributeClusterDimension;
        at.val.clusterDim.x = kG; at.val.clusterDim.y = 1; at.val.clusterDim.z = 1;
        cfg.attrs = &at;
        cfg.numAttrs = 1;
        if (cudaOccupancyMaxActiveClusters(&nclusters, tree_attn_kernel, &cfg) != cudaSuccess || nclusters < 1) {
            (void)cudaGetLastError();
            nclusters = 8;
        }
        if (nclusters > CFG_NC) nclusters = CFG_NC;
        if (nclusters > 1) nclusters &= ~1;
    }
    CUtensorMap tmK, tmV, tmQ;
    make_map(enc, &tmK, k_cache, kPairs * kC, kTileKeys);
    make_map(enc, &tmV, v_cache, kPairs * kC, kTileKeys);
    make_map(enc, &tmQ, q, kPairs * 16, 16);
    tree_attn_kernel<<<kG * nclusters, kThreads, kSmemBytes>>>(tmK, tmV, tmQ, q, k_tree, v_tree, mask, (__nv_bfloat16*)d_out,
                                                      (const __nv_bfloat16*)k_cache);
}
```

```cpp
#include <cuda_runtime.h>
#include <cuda_bf16.h>
#include <cuda.h>
#include <stdint.h>

#define CFG_NS 5
#define CFG_F 5
#define CFG_FMIN 3
#define CFG_W 160
#define CFG_FMIN2 2
#define CFG_W2 260
#define CFG_APF 1
#define CFG_SLEEP 200
#define CFG_PF 2
#define CFG_NC 16
#define CFG_JITTER 0

namespace {

constexpr int kB = 32, kHkv = 16, kT = 8, kC = 2048, kD = 128;
constexpr int kPairs = kB * kHkv;
constexpr int kG = 8;
constexpr int kTileKeys = 64;
constexpr int kTileBytes = kTileKeys * kD * 2;
constexpr int kRun = kC / kG / kTileKeys;
constexpr int kNS = CFG_NS;
constexpr int kF = CFG_F, kFM = CFG_FMIN, kFM2 = CFG_FMIN2;
constexpr int kCW = 4;
constexpr int kWIssue = 4, kWPoll = 5, kWComb = 6;
constexpr int kThreads = 224;
static_assert(kNS <= 8 && kF <= kNS && kF <= 8 && kFM <= kF && kFM2 <= kFM && kFM2 >= 1, "config");

constexpr int kAuxElems = 8192;
constexpr int kAuxPieces = kPairs * 16 * kD / kAuxElems;

constexpr int kRecvBytes = kG * 1024;
constexpr int kMlBytes = kG * 128;

constexpr int kSmRing = 0;
constexpr int kSmQ = kSmRing + kNS * kTileBytes;
constexpr int kSmP = kSmQ + 4096;
constexpr int kSmRecv = kSmP + kRun * kCW * 32 * 16;
constexpr int kSmMl = kSmRecv + 2 * kRecvBytes;
constexpr int kSmMax = kSmMl + 4 * kMlBytes;
constexpr int kSmSum = kSmMax + 16 * kCW * 4;
constexpr int kSmBar = kSmSum + 16 * kCW * 4;
constexpr int kNumBars = 2 * kNS + 2 + 2 + 2 + 4;
constexpr int kSmPace = kSmBar + kNumBars * 8;
constexpr int kSmemBytes = kSmPace + 16;
static_assert(kSmemBytes <= 113 * 1024, "two CTAs must fit one SM");

__device__ __forceinline__ uint32_t smem_u32(const void* p) {
    return (uint32_t)__cvta_generic_to_shared(p);
}
__device__ __forceinline__ void mbar_init(uint32_t bar, int cnt) {
    asm volatile("mbarrier.init.shared::cta.b64 [%0], %1;" ::"r"(bar), "r"(cnt) : "memory");
}
__device__ __forceinline__ void mbar_expect_tx(uint32_t bar, uint32_t bytes) {
    asm volatile("mbarrier.arrive.expect_tx.shared::cta.b64 _, [%0], %1;" ::"r"(bar), "r"(bytes) : "memory");
}
__device__ __forceinline__ void mbar_arrive(uint32_t bar) {
    asm volatile("mbarrier.arrive.shared::cta.b64 _, [%0];" ::"r"(bar) : "memory");
}
__device__ __forceinline__ bool mbar_try(uint32_t bar, uint32_t parity) {
    uint32_t ok;
    asm volatile(
        "{\n.reg .pred p;\n"
        "mbarrier.try_wait.parity.shared::cta.b64 p, [%1], %2;\n"
        "selp.u32 %0, 1, 0, p;\n}"
        : "=r"(ok) : "r"(bar), "r"(parity) : "memory");
    return ok != 0;
}
__device__ __forceinline__ bool mbar_try_cluster(uint32_t bar, uint32_t parity) {
    uint32_t ok;
    asm volatile(
        "{\n.reg .pred p;\n"
        "mbarrier.try_wait.parity.acquire.cluster.shared::cta.b64 p, [%1], %2;\n"
        "selp.u32 %0, 1, 0, p;\n}"
        : "=r"(ok) : "r"(bar), "r"(parity) : "memory");
    return ok != 0;
}
__device__ __forceinline__ bool mbar_test(uint32_t bar, uint32_t parity) {
    uint32_t ok;
    asm volatile(
        "{\n.reg .pred p;\n"
        "mbarrier.test_wait.parity.shared::cta.b64 p, [%1], %2;\n"
        "selp.u32 %0, 1, 0, p;\n}"
        : "=r"(ok) : "r"(bar), "r"(parity) : "memory");
    return ok != 0;
}
__device__ __forceinline__ void mbar_wait(uint32_t bar, uint32_t parity) {
    for (uint32_t it = 0; !mbar_try(bar, parity); ++it)
        if (it > (1u << 22)) __trap();
}
__device__ __forceinline__ void mbar_wait_cluster(uint32_t bar, uint32_t parity) {
    for (uint32_t it = 0; !mbar_try_cluster(bar, parity); ++it)
        if (it > (1u << 22)) __trap();
}
__device__ __forceinline__ uint32_t lds_volatile(uint32_t a) {
    uint32_t v;
    asm volatile("ld.volatile.shared.u32 %0, [%1];" : "=r"(v) : "r"(a) : "memory");
    return v;
}
__device__ __forceinline__ void sts_volatile(uint32_t a, uint32_t v) {
    asm volatile("st.volatile.shared.u32 [%0], %1;" ::"r"(a), "r"(v) : "memory");
}
__device__ __forceinline__ uint32_t mapa(uint32_t addr, uint32_t rank) {
    uint32_t r;
    asm("mapa.shared::cluster.u32 %0, %1, %2;" : "=r"(r) : "r"(addr), "r"(rank));
    return r;
}
__device__ __forceinline__ void st_async4(uint32_t addr, float a, float b, float c, float d, uint32_t bar) {
    asm volatile("st.async.weak.shared::cluster.mbarrier::complete_tx::bytes.v4.f32 [%0], {%1,%2,%3,%4}, [%5];"
                 ::"r"(addr), "f"(a), "f"(b), "f"(c), "f"(d), "r"(bar) : "memory");
}
__device__ __forceinline__ void tma_tile(uint32_t dst, const CUtensorMap* tm, int row, uint32_t bar, uint64_t pol) {
    asm volatile(
        "cp.async.bulk.tensor.3d.shared::cluster.global.mbarrier::complete_tx::bytes.L2::cache_hint "
        "[%0], [%1, {%3, %4, %5}], [%2], %6;"
        ::"r"(dst), "l"(tm), "r"(bar), "r"(0), "r"(row), "r"(0), "l"(pol) : "memory");
}
__device__ __forceinline__ void tma_tile_nohint(uint32_t dst, const CUtensorMap* tm, int row, uint32_t bar) {
    asm volatile(
        "cp.async.bulk.tensor.3d.shared::cluster.global.mbarrier::complete_tx::bytes "
        "[%0], [%1, {%3, %4, %5}], [%2];"
        ::"r"(dst), "l"(tm), "r"(bar), "r"(0), "r"(row), "r"(0) : "memory");
}
__device__ __forceinline__ void l2_prefetch(const void* p) {
    asm volatile("cp.async.bulk.prefetch.L2.global [%0], %1;" ::"l"(p), "n"(kAuxElems * 2) : "memory");
}
__device__ __forceinline__ void ldsm4(uint32_t& r0, uint32_t& r1, uint32_t& r2, uint32_t& r3, uint32_t addr) {
    asm volatile("ldmatrix.sync.aligned.m8n8.x4.shared.b16 {%0,%1,%2,%3}, [%4];"
                 : "=r"(r0), "=r"(r1), "=r"(r2), "=r"(r3) : "r"(addr) : "memory");
}
__device__ __forceinline__ void ldsm4t(uint32_t& r0, uint32_t& r1, uint32_t& r2, uint32_t& r3, uint32_t addr) {
    asm volatile("ldmatrix.sync.aligned.m8n8.x4.trans.shared.b16 {%0,%1,%2,%3}, [%4];"
                 : "=r"(r0), "=r"(r1), "=r"(r2), "=r"(r3) : "r"(addr) : "memory");
}
__device__ __forceinline__ void mma16816(float (&c)[4], uint32_t a0, uint32_t a1, uint32_t a2, uint32_t a3,
                                         uint32_t b0, uint32_t b1) {
    asm("mma.sync.aligned.m16n8k16.row.col.f32.bf16.bf16.f32 {%0,%1,%2,%3}, {%4,%5,%6,%7}, {%8,%9}, {%0,%1,%2,%3};"
        : "+f"(c[0]), "+f"(c[1]), "+f"(c[2]), "+f"(c[3])
        : "r"(a0), "r"(a1), "r"(a2), "r"(a3), "r"(b0), "r"(b1));
}
__device__ __forceinline__ float ex2(float x) {
    float y;
    asm("ex2.approx.ftz.f32 %0, %1;" : "=f"(y) : "f"(x));
    return y;
}
__device__ __forceinline__ uint32_t pack_bf16(float lo, float hi) {
    uint32_t r;
    asm("cvt.rn.bf16x2.f32 %0, %1, %2;" : "=r"(r) : "f"(hi), "f"(lo));
    return r;
}
__device__ __forceinline__ float quad_max(float v) {
    v = fmaxf(v, __shfl_xor_sync(0xffffffffu, v, 1));
    v = fmaxf(v, __shfl_xor_sync(0xffffffffu, v, 2));
    return v;
}
__device__ __forceinline__ float quad_sum(float v) {
    v += __shfl_xor_sync(0xffffffffu, v, 1);
    v += __shfl_xor_sync(0xffffffffu, v, 2);
    return v;
}
__device__ __forceinline__ void jitter(uint32_t salt) {
    (void)salt;
}

__device__ __forceinline__ int tile_pos(int t, int mem) {
    return (mem >> 2) << 4 | t << 2 | (mem & 3);
}

constexpr uint32_t kOnes = 0x3f803f80u;

__device__ unsigned g_progress;

__global__ void __cluster_dims__(kG, 1, 1) __launch_bounds__(kThreads, 2)
tree_attn_kernel(const __grid_constant__ CUtensorMap tmK, const __grid_constant__ CUtensorMap tmV,
                 const __grid_constant__ CUtensorMap tmQ, const __nv_bfloat16* __restrict__ q,
                 const __nv_bfloat16* __restrict__ k_tree, const __nv_bfloat16* __restrict__ v_tree,
                 const __nv_bfloat16* __restrict__ mask, __nv_bfloat16* __restrict__ out,
                 const __nv_bfloat16* __restrict__ kc, int pairs_lo, int pairs_rem) {
    if (threadIdx.x < CFG_PF) {
        const int key = (blockIdx.x / kG) * kC + tile_pos(threadIdx.x, blockIdx.x % kG) * kTileKeys;
        uint64_t p;
        asm volatile("createpolicy.fractional.L2::evict_first.b64 %0, 1.0;" : "=l"(p));
        asm volatile("cp.async.bulk.prefetch.L2.global.L2::cache_hint [%0], %1, %2;"
                     ::"l"(kc + (size_t)key * kD), "r"(kTileBytes), "l"(p) : "memory");
    }
    extern __shared__ __align__(1024) unsigned char sgen[];
    const uint32_t sb = smem_u32(sgen);

    const uint32_t bar_full = sb + kSmBar;
    const uint32_t bar_empty = bar_full + kNS * 8;
    const uint32_t bar_q = bar_empty + kNS * 8;
    const uint32_t bar_rfull = bar_q + 2 * 8;
    const uint32_t bar_cdone = bar_rfull + 2 * 8;
    const uint32_t bar_ml = bar_cdone + 2 * 8;
    const uint32_t s_total = sb + kSmPace, s_stop = s_total + 4;

    const int warp = threadIdx.x >> 5;
    const int lane = threadIdx.x & 31;
    const int cl = blockIdx.x / kG;
    const int mem = blockIdx.x % kG;
    const int nclusters = gridDim.x / kG;
    const int npairs = pairs_lo + (cl < pairs_rem);
    const float c = 0.08838834764831845f * 1.4426950408889634f;

    uint64_t pol = 0;
    auto issue = [&](int j, int slot) {
        const int u = j >> 3;
        const int r = j & 7;
        const int pair = cl + u * nclusters;
        const int t = r & 3;
        const int key = pair * kC + tile_pos(t, mem) * kTileKeys;
        const uint32_t fb = bar_full + slot * 8;
        mbar_expect_tx(fb, kTileBytes);
        tma_tile(sb + kSmRing + slot * kTileBytes, r >= 4 ? &tmV : &tmK, key, fb, pol);
        if (r == 0) {
            mbar_expect_tx(bar_q, 4096);
            tma_tile_nohint(sb + kSmQ, &tmQ, pair * 16, bar_q);
        }
    };

    asm volatile("createpolicy.fractional.L2::evict_first.b64 %0, 1.0;" : "=l"(pol));
    if (threadIdx.x == kWIssue * 32) {
#pragma unroll
        for (int i = 0; i < kF; ++i) mbar_init(bar_full + i * 8, 1);
        mbar_init(bar_q, 1);
        asm volatile("fence.proxy.async.shared::cta;" ::: "memory");
#pragma unroll
        for (int i = 0; i < kF; ++i) issue(i, i);
        for (int s = kF; s < kNS; ++s) mbar_init(bar_full + s * 8, 1);
        for (int s = 0; s < kNS; ++s) mbar_init(bar_empty + s * 8, kCW);
        for (int s = 0; s < 2; ++s) {
            mbar_init(bar_cdone + s * 8, 1);
            mbar_init(bar_rfull + s * 8, 1);
            mbar_expect_tx(bar_rfull + s * 8, kRecvBytes);
        }
        for (int s = 0; s < 4; ++s) {
            mbar_init(bar_ml + s * 8, 1);
            mbar_expect_tx(bar_ml + s * 8, kMlBytes);
        }
        sts_volatile(s_total, 0);
        sts_volatile(s_stop, 0);
        asm volatile("fence.mbarrier_init.release.cluster;" ::: "memory");
        asm volatile("fence.proxy.async.shared::cta;" ::: "memory");
        if (sb & 1023u) __trap();
    }
    __syncthreads();
    asm volatile("barrier.cluster.arrive.relaxed.aligned;" ::: "memory");

    if (warp == kWIssue) {
        if (lane == 0) {
            int si = kF % kNS; uint32_t pe = kF < kNS;
            int sf = 0; uint32_t pf = 0;
            int sm = kF - kFM; uint32_t pm = 0;
            int sn = kF - kFM2; uint32_t pn = 0;
            const int ntiles = npairs * 2 * kRun;
            const int total = kG * (2 * kRun * kPairs - nclusters * kF);
            const float scale = (float)total / (float)(ntiles - kF);
            for (int j = kF; j < ntiles; ++j) {
                mbar_wait(bar_full + sf * 8, pf);
                if (++sf == kNS) { sf = 0; pf ^= 1; }
                asm volatile("red.relaxed.gpu.global.inc.u32 [%0], %1;"
                             ::"l"(&g_progress), "r"((unsigned)(total - 1)) : "memory");
                const int mine = (int)((float)(j - kF + 1) * scale) - CFG_W;
                for (uint32_t it = 0; mine > (int)lds_volatile(s_total) && !mbar_test(bar_full + sm * 8, pm); ++it)
                    if (it > (1u << 26)) __trap();
                if (++sm == kNS) { sm = 0; pm ^= 1; }
                for (uint32_t it = 0;
                     mine - (CFG_W2 - CFG_W) > (int)lds_volatile(s_total) && !mbar_test(bar_full + sn * 8, pn); ++it)
                    if (it > (1u << 26)) __trap();
                if (++sn == kNS) { sn = 0; pn ^= 1; }
                if (j == kF) {
                    for (int i = blockIdx.x; i < kAuxPieces; i += gridDim.x) {
                        l2_prefetch(q + i * kAuxElems);
                        l2_prefetch((i & 1 ? k_tree : v_tree) + (i >> 1) * kAuxElems);
                    }
                }
                mbar_wait(bar_empty + si * 8, pe);
                issue(j, si);
                if (++si == kNS) { si = 0; pe ^= 1; }
            }
            sts_volatile(s_stop, 1);
        }
    } else if (warp == kWPoll) {
        if (lane == 0) {
            for (uint32_t it = 0; lds_volatile(s_stop) == 0 && it < (1u << 24); ++it) {
                unsigned t;
                asm volatile("ld.relaxed.gpu.global.u32 %0, [%1];" : "=r"(t) : "l"(&g_progress) : "memory");
                sts_volatile(s_total, t);
                __nanosleep(CFG_SLEEP);
            }
        }
    } else if (warp == kWComb) {
        const int g = lane >> 2, tq = lane & 3;
        uint4 qa[4], qb[4], kt[4];
        uint32_t vt[2], mk;
        auto fetch = [&](int u) {
            const int pair = cl + u * nclusters;
            const uint4* qp = reinterpret_cast<const uint4*>(q + ((size_t)pair * 16 + g) * kD) + tq;
            const uint4* kp = reinterpret_cast<const uint4*>(k_tree + ((size_t)pair * kT + g) * kD) + tq;
#pragma unroll
            for (int j = 0; j < 4; ++j) {
                qa[j] = __ldg(qp + 4 * j);
                qb[j] = __ldg(qp + 4 * j + 8 * kD / 8);
                kt[j] = __ldg(kp + 4 * j);
            }
            const unsigned short* vp =
                reinterpret_cast<const unsigned short*>(v_tree) + ((size_t)pair * kT + 2 * tq) * kD + 16 * mem + g;
#pragma unroll
            for (int n = 0; n < 2; ++n)
                vt[n] = (uint32_t)__ldg(vp + 8 * n) | ((uint32_t)__ldg(vp + 8 * n + kD) << 16);
            mk = __ldg(reinterpret_cast<const uint32_t*>(mask + (size_t)(pair / kHkv) * kT * kT + g * kT + 2 * tq));
        };
        fetch(0);
        for (int u = 0; u < npairs; ++u) {
            const int s = u & 1;
            const int pair = cl + u * nclusters;
            float acc[2][4], lt[4] = {0.f, 0.f, 0.f, 0.f}, mt0, mt1;
            {
                float st[4] = {0.f, 0.f, 0.f, 0.f};
#pragma unroll
                for (int j = 0; j < 4; ++j) {
                    mma16816(st, qa[j].x, qb[j].x, qa[j].y, qb[j].y, kt[j].x, kt[j].y);
                    mma16816(st, qa[j].z, qb[j].z, qa[j].w, qb[j].w, kt[j].z, kt[j].w);
                }
                const float bias0 = (1.0f - __uint_as_float(mk << 16)) * (-1.0e9f * 1.4426950408889634f);
                const float bias1 = (1.0f - __uint_as_float(mk & 0xffff0000u)) * (-1.0e9f * 1.4426950408889634f);
                const float t0 = fmaf(st[0], c, bias0), t1 = fmaf(st[1], c, bias1);
                const float t2 = fmaf(st[2], c, bias0), t3 = fmaf(st[3], c, bias1);
                mt0 = quad_max(fmaxf(t0, t1));
                mt1 = quad_max(fmaxf(t2, t3));
                const uint32_t a0 = pack_bf16(ex2(t0 - mt0), ex2(t1 - mt0));
                const uint32_t a1 = pack_bf16(ex2(t2 - mt1), ex2(t3 - mt1));
#pragma unroll
                for (int n = 0; n < 2; ++n) {
                    acc[n][0] = 0.f; acc[n][1] = 0.f; acc[n][2] = 0.f; acc[n][3] = 0.f;
                    mma16816(acc[n], a0, a1, 0u, 0u, vt[n], 0u);
                }
                mma16816(lt, a0, a1, 0u, 0u, kOnes, 0u);
            }
            if (u + 1 < npairs) fetch(u + 1);
            jitter(1);

            float w0[kG], w1[kG];
            mbar_wait_cluster(bar_ml + (u & 3) * 8, (u >> 2) & 1);
            {
                float4 ml[kG];
#pragma unroll
                for (int j = 0; j < kG; ++j)
                    ml[j] = *reinterpret_cast<const float4*>(sgen + kSmMl + (u & 3) * kMlBytes + j * 128 + g * 16);
                float M0 = mt0, M1 = mt1;
#pragma unroll
                for (int j = 0; j < kG; ++j) { M0 = fmaxf(M0, ml[j].x); M1 = fmaxf(M1, ml[j].z); }
                const float wt0 = ex2(mt0 - M0), wt1 = ex2(mt1 - M1);
                float L0 = lt[0] * wt0, L1 = lt[2] * wt1;
#pragma unroll
                for (int j = 0; j < kG; ++j) {
                    w0[j] = ex2(ml[j].x - M0);
                    w1[j] = ex2(ml[j].z - M1);
                    L0 = fmaf(ml[j].y, w0[j], L0);
                    L1 = fmaf(ml[j].w, w1[j], L1);
                }
                const float inv0 = 1.0f / L0, inv1 = 1.0f / L1;
#pragma unroll
                for (int j = 0; j < kG; ++j) { w0[j] *= inv0; w1[j] *= inv1; }
#pragma unroll
                for (int n = 0; n < 2; ++n) {
                    acc[n][0] *= wt0 * inv0; acc[n][1] *= wt0 * inv0;
                    acc[n][2] *= wt1 * inv1; acc[n][3] *= wt1 * inv1;
                }
            }
            __syncwarp();
            if (lane == 0) mbar_expect_tx(bar_ml + (u & 3) * 8, kMlBytes);
            jitter(2);

            mbar_wait_cluster(bar_rfull + s * 8, (u >> 1) & 1);
            const unsigned char* rb = sgen + kSmRecv + s * kRecvBytes;
#pragma unroll
            for (int j = 0; j < kG; ++j)
#pragma unroll
                for (int n = 0; n < 2; ++n) {
                    const float4 v = *reinterpret_cast<const float4*>(rb + ((j * 2 + n) * 32 + lane) * 16);
                    acc[n][0] = fmaf(v.x, w0[j], acc[n][0]); acc[n][1] = fmaf(v.y, w0[j], acc[n][1]);
                    acc[n][2] = fmaf(v.z, w1[j], acc[n][2]); acc[n][3] = fmaf(v.w, w1[j], acc[n][3]);
                }
            uint32_t* o0 = reinterpret_cast<uint32_t*>(out + ((size_t)pair * 16 + g) * kD + 16 * mem + 2 * tq);
#pragma unroll
            for (int n = 0; n < 2; ++n) {
                o0[4 * n] = pack_bf16(acc[n][0], acc[n][1]);
                o0[4 * n + 8 * kD / 2] = pack_bf16(acc[n][2], acc[n][3]);
            }
            jitter(6);
            __syncwarp();
            if (lane == 0) {
                mbar_expect_tx(bar_rfull + s * 8, kRecvBytes);
                mbar_arrive(bar_cdone + s * 8);
            }
        }
    } else {
        const int g = lane >> 2;
        const int tq = lane & 3;
        const int mi = lane >> 3;
        const int lr = lane & 7;

        const uint32_t k_row = (uint32_t)(16 * warp + 8 * (mi >> 1) + lr) * 128u;
        const uint32_t k_x = (uint32_t)(((mi & 1) ^ lr) << 4);
        const uint32_t q_row = (uint32_t)(8 * (mi & 1) + lr) * 128u;
        const uint32_t q_x = (uint32_t)(((mi >> 1) ^ lr) << 4);
        const uint32_t v_row = (uint32_t)(warp >> 1) * 8192u + (uint32_t)(8 * (mi & 1) + lr) * 128u;
        const uint32_t v_x0 = (uint32_t)(((4 * (warp & 1) + (mi >> 1)) ^ lr) << 4);
        const uint32_t v_x1 = v_x0 ^ 32u;

        uint4* const pbuf = reinterpret_cast<uint4*>(sgen + kSmP);
        float* const smax = reinterpret_cast<float*>(sgen + kSmMax);
        float* const ssum = reinterpret_cast<float*>(sgen + kSmSum);

        const uint32_t rem0 = mapa(sb, 2 * warp), rem1 = mapa(sb, 2 * warp + 1);
        const uint32_t rem_ml = (tq == 0 ? rem0 : rem1);

        int slot = 0;
        uint32_t phase = 0;

        auto release = [&](int sl) {
            __syncwarp();
            if (lane == 0) mbar_arrive(bar_empty + sl * 8);
        };
        auto load_k = [&](uint32_t (&f)[8][4], int sl) {
            const uint32_t base = sb + kSmRing + sl * kTileBytes + k_row;
#pragma unroll
            for (int ks = 0; ks < 8; ++ks)
                ldsm4(f[ks][0], f[ks][1], f[ks][2], f[ks][3], base + (ks >> 2) * 8192 + (k_x ^ ((ks & 3) << 5)));
        };
        auto load_v = [&](uint32_t (&f)[8][4], int sl) {
            const uint32_t base = sb + kSmRing + sl * kTileBytes + v_row;
#pragma unroll
            for (int ks = 0; ks < 4; ++ks) {
                ldsm4t(f[2 * ks][0], f[2 * ks][1], f[2 * ks][2], f[2 * ks][3], base + ks * 2048 + v_x0);
                ldsm4t(f[2 * ks + 1][0], f[2 * ks + 1][1], f[2 * ks + 1][2], f[2 * ks + 1][3], base + ks * 2048 + v_x1);
            }
        };

        for (int u = 0; u < npairs; ++u) {
            mbar_wait(bar_q, u & 1);
            uint32_t qf[8][4];
            {
                const uint32_t qa = sb + kSmQ + q_row;
#pragma unroll
                for (int ks = 0; ks < 8; ++ks)
                    ldsm4(qf[ks][0], qf[ks][1], qf[ks][2], qf[ks][3], qa + (ks >> 2) * 2048 + (q_x ^ ((ks & 3) << 5)));
            }
            float s[kRun][2][4];
            auto qk = [&](const uint32_t (&f)[8][4], float (&d)[2][4]) {
                float h[2][4];
#pragma unroll
                for (int e = 0; e < 4; ++e) { d[0][e] = 0.f; d[1][e] = 0.f; h[0][e] = 0.f; h[1][e] = 0.f; }
#pragma unroll
                for (int ks = 0; ks < 8; ks += 2) {
                    mma16816(d[0], qf[ks][0], qf[ks][1], qf[ks][2], qf[ks][3], f[ks][0], f[ks][1]);
                    mma16816(d[1], qf[ks][0], qf[ks][1], qf[ks][2], qf[ks][3], f[ks][2], f[ks][3]);
                    mma16816(h[0], qf[ks + 1][0], qf[ks + 1][1], qf[ks + 1][2], qf[ks + 1][3], f[ks + 1][0], f[ks + 1][1]);
                    mma16816(h[1], qf[ks + 1][0], qf[ks + 1][1], qf[ks + 1][2], qf[ks + 1][3], f[ks + 1][2], f[ks + 1][3]);
                }
#pragma unroll
                for (int e = 0; e < 4; ++e) { d[0][e] += h[0][e]; d[1][e] += h[1][e]; }
            };
#pragma unroll
            for (int t = 0; t < kRun; ++t) {
                uint32_t f[8][4];
                mbar_wait(bar_full + slot * 8, phase);
                load_k(f, slot);
                release(slot);
                qk(f, s[t]);
                if (++slot == kNS) { slot = 0; phase ^= 1; }
            }
            jitter(3);
            float x0 = fmaxf(s[0][0][0], s[0][0][1]), x1 = fmaxf(s[0][0][2], s[0][0][3]);
#pragma unroll
            for (int t = 0; t < kRun; ++t)
#pragma unroll
                for (int n = 0; n < 2; ++n) {
                    x0 = fmaxf(x0, fmaxf(s[t][n][0], s[t][n][1]));
                    x1 = fmaxf(x1, fmaxf(s[t][n][2], s[t][n][3]));
                }
            x0 = quad_max(x0);
            x1 = quad_max(x1);
            if (tq == 0) {
                smax[g * kCW + warp] = x0;
                smax[(g + 8) * kCW + warp] = x1;
            }
            asm volatile("bar.sync 1, %0;" ::"n"(kCW * 32) : "memory");
            {
                const float4 a = *reinterpret_cast<const float4*>(smax + g * kCW);
                const float4 b = *reinterpret_cast<const float4*>(smax + (g + 8) * kCW);
                x0 = fmaxf(fmaxf(a.x, a.y), fmaxf(a.z, a.w));
                x1 = fmaxf(fmaxf(b.x, b.y), fmaxf(b.z, b.w));
            }
            const float m0 = x0 * c, m1 = x1 * c;
            float r0 = 0.f, r1 = 0.f;
#pragma unroll
            for (int t = 0; t < kRun; ++t) {
                uint32_t pf[4];
#pragma unroll
                for (int n = 0; n < 2; ++n) {
                    const float p0 = ex2(fmaf(s[t][n][0], c, -m0)), p1 = ex2(fmaf(s[t][n][1], c, -m0));
                    const float p2 = ex2(fmaf(s[t][n][2], c, -m1)), p3 = ex2(fmaf(s[t][n][3], c, -m1));
                    r0 += p0 + p1;
                    r1 += p2 + p3;
                    pf[2 * n] = pack_bf16(p0, p1);
                    pf[2 * n + 1] = pack_bf16(p2, p3);
                }
                pbuf[(t * kCW + warp) * 32 + lane] = make_uint4(pf[0], pf[1], pf[2], pf[3]);
            }
            r0 = quad_sum(r0);
            r1 = quad_sum(r1);
            if (tq == 0) {
                ssum[g * kCW + warp] = r0;
                ssum[(g + 8) * kCW + warp] = r1;
            }
            asm volatile("bar.sync 1, %0;" ::"n"(kCW * 32) : "memory");
            jitter(4);
            {
                const float4 a = *reinterpret_cast<const float4*>(ssum + g * kCW);
                const float4 b = *reinterpret_cast<const float4*>(ssum + (g + 8) * kCW);
                if (u == 0) asm volatile("barrier.cluster.wait.acquire.aligned;" ::: "memory");
                if (tq < 2)
                    st_async4(rem_ml + kSmMl + (u & 3) * kMlBytes + mem * 128 + g * 16, m0, (a.x + a.y) + (a.z + a.w), m1,
                              (b.x + b.y) + (b.z + b.w), rem_ml + kSmBar + (2 * kNS + 6 + (u & 3)) * 8);
            }
            float o[2][4][4];
#pragma unroll
            for (int n = 0; n < 8; ++n) { o[n >> 2][n & 3][0] = 0.f; o[n >> 2][n & 3][1] = 0.f; o[n >> 2][n & 3][2] = 0.f; o[n >> 2][n & 3][3] = 0.f; }
            auto pv = [&](const uint32_t (&f)[8][4], const uint4* pa) {
#pragma unroll
                for (int ks = 0; ks < 4; ++ks) {
                    const uint4 a = pa[ks];
                    mma16816(o[ks & 1][0], a.x, a.y, a.z, a.w, f[2 * ks][0], f[2 * ks][1]);
                    mma16816(o[ks & 1][1], a.x, a.y, a.z, a.w, f[2 * ks][2], f[2 * ks][3]);
                    mma16816(o[ks & 1][2], a.x, a.y, a.z, a.w, f[2 * ks + 1][0], f[2 * ks + 1][1]);
                    mma16816(o[ks & 1][3], a.x, a.y, a.z, a.w, f[2 * ks + 1][2], f[2 * ks + 1][3]);
                }
            };
#pragma unroll
            for (int t = 0; t < kRun; ++t) {
                uint32_t f[8][4];
                uint4 pa[kCW];
#pragma unroll
                for (int i = 0; i < kCW; ++i) pa[i] = pbuf[(t * kCW + i) * 32 + lane];
                if (t == kRun - 1 && u > 0) mbar_wait(bar_cdone + ((u - 1) & 1) * 8, ((u - 1) >> 1) & 1);
                mbar_wait(bar_full + slot * 8, phase);
                load_v(f, slot);
                release(slot);
                pv(f, pa);
                if (++slot == kNS) { slot = 0; phase ^= 1; }
            }
            jitter(5);
            {
                const uint32_t doff = kSmRecv + (u & 1) * kRecvBytes + (uint32_t)(mem * 64 + lane) * 16u;
                const uint32_t boff = kSmBar + (2 * kNS + 2 + (u & 1)) * 8;
#pragma unroll
                for (int n = 0; n < 4; ++n) {
                    const uint32_t rem = n < 2 ? rem0 : rem1;
                    st_async4(rem + doff + (n & 1) * 512, o[0][n][0] + o[1][n][0], o[0][n][1] + o[1][n][1],
                              o[0][n][2] + o[1][n][2], o[0][n][3] + o[1][n][3], rem + boff);
                }
            }
        }
    }
}

typedef CUresult (*EncodeTiledFn)(CUtensorMap*, CUtensorMapDataType, cuuint32_t, void*, const cuuint64_t*,
                                  const cuuint64_t*, const cuuint32_t*, const cuuint32_t*, CUtensorMapInterleave,
                                  CUtensorMapSwizzle, CUtensorMapL2promotion, CUtensorMapFloatOOBfill);

void make_map(EncodeTiledFn enc, CUtensorMap* tm, const void* base, int rows, int box_rows) {
    cuuint64_t dims[3] = {64, (cuuint64_t)rows, 2};
    cuuint64_t strides[2] = {256, 128};
    cuuint32_t box[3] = {64, (cuuint32_t)box_rows, 2};
    cuuint32_t es[3] = {1, 1, 1};
    enc(tm, CU_TENSOR_MAP_DATA_TYPE_BFLOAT16, 3, const_cast<void*>(base), dims, strides, box, es,
        CU_TENSOR_MAP_INTERLEAVE_NONE, CU_TENSOR_MAP_SWIZZLE_128B, CU_TENSOR_MAP_L2_PROMOTION_L2_256B,
        CU_TENSOR_MAP_FLOAT_OOB_FILL_NONE);
}

}

extern "C" void kernel_launch(void* const* d_in, const int* in_sizes, int n_in, void* d_out, int out_size) {
    (void)in_sizes; (void)n_in; (void)out_size;
    const __nv_bfloat16* q = (const __nv_bfloat16*)d_in[0];
    const void* k_cache = d_in[1];
    const void* v_cache = d_in[2];
    const __nv_bfloat16* k_tree = (const __nv_bfloat16*)d_in[3];
    const __nv_bfloat16* v_tree = (const __nv_bfloat16*)d_in[4];
    const __nv_bfloat16* mask = (const __nv_bfloat16*)d_in[5];

    static EncodeTiledFn enc = nullptr;
    static int nclusters = 0;
    if (!enc) {
        void* fn = nullptr;
        cudaDriverEntryPointQueryResult qr;
        cudaGetDriverEntryPoint("cuTensorMapEncodeTiled", &fn, cudaEnableDefault, &qr);
        enc = (EncodeTiledFn)fn;
        cudaFuncSetAttribute(tree_attn_kernel, cudaFuncAttributeMaxDynamicSharedMemorySize, kSmemBytes);
        cudaLaunchConfig_t cfg = {};
        cfg.gridDim = dim3(kG * CFG_NC);
        cfg.blockDim = dim3(kThreads);
        cfg.dynamicSmemBytes = kSmemBytes;
        cudaLaunchAttribute at;
        at.id = cudaLaunchAttributeClusterDimension;
        at.val.clusterDim.x = kG; at.val.clusterDim.y = 1; at.val.clusterDim.z = 1;
        cfg.attrs = &at;
        cfg.numAttrs = 1;
        if (cudaOccupancyMaxActiveClusters(&nclusters, tree_attn_kernel, &cfg) != cudaSuccess || nclusters < 1) {
            (void)cudaGetLastError();
            nclusters = 8;
        }
        if (nclusters > CFG_NC) nclusters = CFG_NC;
        if (nclusters > 1) nclusters &= ~1;
    }
    CUtensorMap tmK, tmV, tmQ;
    make_map(enc, &tmK, k_cache, kPairs * kC, kTileKeys);
    make_map(enc, &tmV, v_cache, kPairs * kC, kTileKeys);
    make_map(enc, &tmQ, q, kPairs * 16, 16);
    tree_attn_kernel<<<kG * nclusters, kThreads, kSmemBytes>>>(tmK, tmV, tmQ, q, k_tree, v_tree, mask,
                                                              (__nv_bfloat16*)d_out, (const __nv_bfloat16*)k_cache,
                                                              kPairs / nclusters, kPairs % nclusters);
}
```

```cpp
#include <cuda_runtime.h>
#include <cuda_bf16.h>
#include <cuda.h>
#include <stdint.h>

#define CFG_NS 5
#define CFG_F 5
#define CFG_FMIN 3
#define CFG_W 160
#define CFG_FMIN2 2
#define CFG_W2 260
#define CFG_APF 1
#define CFG_SLEEP 200
#define CFG_PF 2
#define CFG_NC 16
#define CFG_JITTER 0

namespace {

constexpr int kB = 32, kHkv = 16, kT = 8, kC = 2048, kD = 128;
constexpr int kPairs = kB * kHkv;
constexpr int kG = 8;
constexpr int kTileKeys = 64;
constexpr int kTileBytes = kTileKeys * kD * 2;
constexpr int kRun = kC / kG / kTileKeys;
constexpr int kNS = CFG_NS;
constexpr int kF = CFG_F, kFM = CFG_FMIN, kFM2 = CFG_FMIN2;
constexpr int kCW = 4;
constexpr int kWIssue = 4, kWPoll = 5, kWComb = 6;
constexpr int kThreads = 224;
static_assert(kNS <= 8 && kF <= kNS && kF <= 8 && kFM <= kF && kFM2 <= kFM && kFM2 >= 1, "config");

constexpr int kAuxElems = 8192;
constexpr int kAuxPieces = kPairs * 16 * kD / kAuxElems;

constexpr int kRecvBytes = kG * 1024;
constexpr int kMlBytes = kG * 128;

constexpr int kSmRing = 0;
constexpr int kSmQ = kSmRing + kNS * kTileBytes;
constexpr int kSmP = kSmQ + 4096;
constexpr int kSmRecv = kSmP + kRun * kCW * 32 * 16;
constexpr int kSmMl = kSmRecv + 2 * kRecvBytes;
constexpr int kSmMax = kSmMl + 4 * kMlBytes;
constexpr int kSmSum = kSmMax + 16 * kCW * 4;
constexpr int kSmBar = kSmSum + 16 * kCW * 4;
constexpr int kNumBars = 2 * kNS + 2 + 2 + 2 + 4;
constexpr int kSmPace = kSmBar + kNumBars * 8;
constexpr int kSmemBytes = kSmPace + 16;
static_assert(kSmemBytes <= 113 * 1024, "two CTAs must fit one SM");

__device__ __forceinline__ uint32_t smem_u32(const void* p) {
    return (uint32_t)__cvta_generic_to_shared(p);
}
__device__ __forceinline__ void mbar_init(uint32_t bar, int cnt) {
    asm volatile("mbarrier.init.shared::cta.b64 [%0], %1;" ::"r"(bar), "r"(cnt) : "memory");
}
__device__ __forceinline__ void mbar_expect_tx(uint32_t bar, uint32_t bytes) {
    asm volatile("mbarrier.arrive.expect_tx.shared::cta.b64 _, [%0], %1;" ::"r"(bar), "r"(bytes) : "memory");
}
__device__ __forceinline__ void mbar_arrive(uint32_t bar) {
    asm volatile("mbarrier.arrive.shared::cta.b64 _, [%0];" ::"r"(bar) : "memory");
}
__device__ __forceinline__ bool mbar_try(uint32_t bar, uint32_t parity) {
    uint32_t ok;
    asm volatile(
        "{\n.reg .pred p;\n"
        "mbarrier.try_wait.parity.shared::cta.b64 p, [%1], %2;\n"
        "selp.u32 %0, 1, 0, p;\n}"
        : "=r"(ok) : "r"(bar), "r"(parity) : "memory");
    return ok != 0;
}
__device__ __forceinline__ bool mbar_try_cluster(uint32_t bar, uint32_t parity) {
    uint32_t ok;
    asm volatile(
        "{\n.reg .pred p;\n"
        "mbarrier.try_wait.parity.acquire.cluster.shared::cta.b64 p, [%1], %2;\n"
        "selp.u32 %0, 1, 0, p;\n}"
        : "=r"(ok) : "r"(bar), "r"(parity) : "memory");
    return ok != 0;
}
__device__ __forceinline__ bool mbar_test(uint32_t bar, uint32_t parity) {
    uint32_t ok;
    asm volatile(
        "{\n.reg .pred p;\n"
        "mbarrier.test_wait.parity.shared::cta.b64 p, [%1], %2;\n"
        "selp.u32 %0, 1, 0, p;\n}"
        : "=r"(ok) : "r"(bar), "r"(parity) : "memory");
    return ok != 0;
}
__device__ __forceinline__ void mbar_wait(uint32_t bar, uint32_t parity) {
    for (uint32_t it = 0; !mbar_try(bar, parity); ++it)
        if (it > (1u << 22)) __trap();
}
__device__ __forceinline__ void mbar_wait_cluster(uint32_t bar, uint32_t parity) {
    for (uint32_t it = 0; !mbar_try_cluster(bar, parity); ++it)
        if (it > (1u << 22)) __trap();
}
__device__ __forceinline__ uint32_t lds_volatile(uint32_t a) {
    uint32_t v;
    asm volatile("ld.volatile.shared.u32 %0, [%1];" : "=r"(v) : "r"(a) : "memory");
    return v;
}
__device__ __forceinline__ void sts_volatile(uint32_t a, uint32_t v) {
    asm volatile("st.volatile.shared.u32 [%0], %1;" ::"r"(a), "r"(v) : "memory");
}
__device__ __forceinline__ uint32_t mapa(uint32_t addr, uint32_t rank) {
    uint32_t r;
    asm("mapa.shared::cluster.u32 %0, %1, %2;" : "=r"(r) : "r"(addr), "r"(rank));
    return r;
}
__device__ __forceinline__ void st_async4(uint32_t addr, float a, float b, float c, float d, uint32_t bar) {
    asm volatile("st.async.weak.shared::cluster.mbarrier::complete_tx::bytes.v4.f32 [%0], {%1,%2,%3,%4}, [%5];"
                 ::"r"(addr), "f"(a), "f"(b), "f"(c), "f"(d), "r"(bar) : "memory");
}
__device__ __forceinline__ void tma_tile(uint32_t dst, const CUtensorMap* tm, int row, uint32_t bar, uint64_t pol) {
    asm volatile(
        "cp.async.bulk.tensor.3d.shared::cluster.global.mbarrier::complete_tx::bytes.L2::cache_hint "
        "[%0], [%1, {%3, %4, %5}], [%2], %6;"
        ::"r"(dst), "l"(tm), "r"(bar), "r"(0), "r"(row), "r"(0), "l"(pol) : "memory");
}
__device__ __forceinline__ void tma_tile_nohint(uint32_t dst, const CUtensorMap* tm, int row, uint32_t bar) {
    asm volatile(
        "cp.async.bulk.tensor.3d.shared::cluster.global.mbarrier::complete_tx::bytes "
        "[%0], [%1, {%3, %4, %5}], [%2];"
        ::"r"(dst), "l"(tm), "r"(bar), "r"(0), "r"(row), "r"(0) : "memory");
}
__device__ __forceinline__ void l2_prefetch(const void* p) {
    asm volatile("cp.async.bulk.prefetch.L2.global [%0], %1;" ::"l"(p), "n"(kAuxElems * 2) : "memory");
}
__device__ __forceinline__ void ldsm4(uint32_t& r0, uint32_t& r1, uint32_t& r2, uint32_t& r3, uint32_t addr) {
    asm volatile("ldmatrix.sync.aligned.m8n8.x4.shared.b16 {%0,%1,%2,%3}, [%4];"
                 : "=r"(r0), "=r"(r1), "=r"(r2), "=r"(r3) : "r"(addr) : "memory");
}
__device__ __forceinline__ void ldsm4t(uint32_t& r0, uint32_t& r1, uint32_t& r2, uint32_t& r3, uint32_t addr) {
    asm volatile("ldmatrix.sync.aligned.m8n8.x4.trans.shared.b16 {%0,%1,%2,%3}, [%4];"
                 : "=r"(r0), "=r"(r1), "=r"(r2), "=r"(r3) : "r"(addr) : "memory");
}
__device__ __forceinline__ void mma16816(float (&c)[4], uint32_t a0, uint32_t a1, uint32_t a2, uint32_t a3,
                                         uint32_t b0, uint32_t b1) {
    asm("mma.sync.aligned.m16n8k16.row.col.f32.bf16.bf16.f32 {%0,%1,%2,%3}, {%4,%5,%6,%7}, {%8,%9}, {%0,%1,%2,%3};"
        : "+f"(c[0]), "+f"(c[1]), "+f"(c[2]), "+f"(c[3])
        : "r"(a0), "r"(a1), "r"(a2), "r"(a3), "r"(b0), "r"(b1));
}
__device__ __forceinline__ float ex2(float x) {
    float y;
    asm("ex2.approx.ftz.f32 %0, %1;" : "=f"(y) : "f"(x));
    return y;
}
__device__ __forceinline__ uint32_t pack_bf16(float lo, float hi) {
    uint32_t r;
    asm("cvt.rn.bf16x2.f32 %0, %1, %2;" : "=r"(r) : "f"(hi), "f"(lo));
    return r;
}
__device__ __forceinline__ float quad_max(float v) {
    v = fmaxf(v, __shfl_xor_sync(0xffffffffu, v, 1));
    v = fmaxf(v, __shfl_xor_sync(0xffffffffu, v, 2));
    return v;
}
__device__ __forceinline__ float quad_sum(float v) {
    v += __shfl_xor_sync(0xffffffffu, v, 1);
    v += __shfl_xor_sync(0xffffffffu, v, 2);
    return v;
}
__device__ __forceinline__ void jitter(uint32_t salt) {
    (void)salt;
}

__device__ __forceinline__ int tile_pos(int t, int mem) {
    return (mem >> 2) << 4 | t << 2 | (mem & 3);
}

constexpr uint32_t kOnes = 0x3f803f80u;

__device__ unsigned g_progress;

__global__ void __cluster_dims__(kG, 1, 1) __launch_bounds__(kThreads, 2)
tree_attn_kernel(const __grid_constant__ CUtensorMap tmK, const __grid_constant__ CUtensorMap tmV,
                 const __grid_constant__ CUtensorMap tmQ, const __nv_bfloat16* __restrict__ q,
                 const __nv_bfloat16* __restrict__ k_tree, const __nv_bfloat16* __restrict__ v_tree,
                 const __nv_bfloat16* __restrict__ mask, __nv_bfloat16* __restrict__ out,
                 const __nv_bfloat16* __restrict__ kc, unsigned* progress, int pairs_lo, int pairs_rem) {
    if (threadIdx.x < CFG_PF) {
        const int key = (blockIdx.x / kG) * kC + tile_pos(threadIdx.x, blockIdx.x % kG) * kTileKeys;
        uint64_t p;
        asm volatile("createpolicy.fractional.L2::evict_first.b64 %0, 1.0;" : "=l"(p));
        asm volatile("cp.async.bulk.prefetch.L2.global.L2::cache_hint [%0], %1, %2;"
                     ::"l"(kc + (size_t)key * kD), "r"(kTileBytes), "l"(p) : "memory");
    }
    extern __shared__ __align__(1024) unsigned char sgen[];
    const uint32_t sb = smem_u32(sgen);

    const uint32_t bar_full = sb + kSmBar;
    const uint32_t bar_empty = bar_full + kNS * 8;
    const uint32_t bar_q = bar_empty + kNS * 8;
    const uint32_t bar_rfull = bar_q + 2 * 8;
    const uint32_t bar_cdone = bar_rfull + 2 * 8;
    const uint32_t bar_ml = bar_cdone + 2 * 8;
    const uint32_t s_total = sb + kSmPace, s_stop = s_total + 4;

    const int warp = threadIdx.x >> 5;
    const int lane = threadIdx.x & 31;
    const int cl = blockIdx.x / kG;
    const int mem = blockIdx.x % kG;
    const int nclusters = gridDim.x / kG;
    const int npairs = pairs_lo + (cl < pairs_rem);
    const float c = 0.08838834764831845f * 1.4426950408889634f;

    uint64_t pol = 0;
    auto issue = [&](int j, int slot) {
        const int u = j >> 3;
        const int r = j & 7;
        const int pair = cl + u * nclusters;
        const int t = r & 3;
        const int key = pair * kC + tile_pos(t, mem) * kTileKeys;
        const uint32_t fb = bar_full + slot * 8;
        mbar_expect_tx(fb, kTileBytes);
        tma_tile(sb + kSmRing + slot * kTileBytes, r >= 4 ? &tmV : &tmK, key, fb, pol);
        if (r == 0) {
            mbar_expect_tx(bar_q, 4096);
            tma_tile_nohint(sb + kSmQ, &tmQ, pair * 16, bar_q);
        }
    };

    asm volatile("createpolicy.fractional.L2::evict_first.b64 %0, 1.0;" : "=l"(pol));
    if (threadIdx.x == kWIssue * 32) {
#pragma unroll
        for (int i = 0; i < kF; ++i) mbar_init(bar_full + i * 8, 1);
        mbar_init(bar_q, 1);
        asm volatile("fence.proxy.async.shared::cta;" ::: "memory");
#pragma unroll
        for (int i = 0; i < kF; ++i) issue(i, i);
        for (int s = kF; s < kNS; ++s) mbar_init(bar_full + s * 8, 1);
        for (int s = 0; s < kNS; ++s) mbar_init(bar_empty + s * 8, kCW);
        for (int s = 0; s < 2; ++s) {
            mbar_init(bar_cdone + s * 8, 1);
            mbar_init(bar_rfull + s * 8, 1);
            mbar_expect_tx(bar_rfull + s * 8, kRecvBytes);
        }
        for (int s = 0; s < 4; ++s) {
            mbar_init(bar_ml + s * 8, 1);
            mbar_expect_tx(bar_ml + s * 8, kMlBytes);
        }
        sts_volatile(s_total, 0);
        sts_volatile(s_stop, 0);
        asm volatile("fence.mbarrier_init.release.cluster;" ::: "memory");
        asm volatile("fence.proxy.async.shared::cta;" ::: "memory");
        if (sb & 1023u) __trap();
    }
    __syncthreads();
    asm volatile("barrier.cluster.arrive.relaxed.aligned;" ::: "memory");

    if (warp == kWIssue) {
        if (lane == 0) {
            int si = kF % kNS; uint32_t pe = kF < kNS;
            int sf = 0; uint32_t pf = 0;
            int sm = kF - kFM; uint32_t pm = 0;
            int sn = kF - kFM2; uint32_t pn = 0;
            const int ntiles = npairs * 2 * kRun;
            const int total = kG * (2 * kRun * kPairs - nclusters * kF);
            const float scale = (float)total / (float)(ntiles - kF);
            for (int j = kF; j < ntiles; ++j) {
                mbar_wait(bar_full + sf * 8, pf);
                if (++sf == kNS) { sf = 0; pf ^= 1; }
                asm volatile("red.relaxed.gpu.global.inc.u32 [%0], %1;"
                             ::"l"(progress), "r"((unsigned)(total - 1)) : "memory");
                const int mine = (int)((float)(j - kF + 1) * scale) - CFG_W;
                for (uint32_t it = 0; mine > (int)lds_volatile(s_total) && !mbar_test(bar_full + sm * 8, pm); ++it)
                    if (it > (1u << 26)) __trap();
                if (++sm == kNS) { sm = 0; pm ^= 1; }
                for (uint32_t it = 0;
                     mine - (CFG_W2 - CFG_W) > (int)lds_volatile(s_total) && !mbar_test(bar_full + sn * 8, pn); ++it)
                    if (it > (1u << 26)) __trap();
                if (++sn == kNS) { sn = 0; pn ^= 1; }
                if (j == kF) {
                    for (int i = blockIdx.x; i < kAuxPieces; i += gridDim.x) {
                        l2_prefetch(q + i * kAuxElems);
                        l2_prefetch((i & 1 ? k_tree : v_tree) + (i >> 1) * kAuxElems);
                    }
                }
                mbar_wait(bar_empty + si * 8, pe);
                issue(j, si);
                if (++si == kNS) { si = 0; pe ^= 1; }
            }
            sts_volatile(s_stop, 1);
        }
    } else if (warp == kWPoll) {
        if (lane == 0) {
            for (uint32_t it = 0; lds_volatile(s_stop) == 0 && it < (1u << 24); ++it) {
                unsigned t;
                asm volatile("ld.relaxed.gpu.global.u32 %0, [%1];" : "=r"(t) : "l"(progress) : "memory");
                sts_volatile(s_total, t);
                __nanosleep(CFG_SLEEP);
            }
        }
    } else if (warp == kWComb) {
        const int g = lane >> 2, tq = lane & 3;
        uint4 qa[4], qb[4], kt[4];
        uint32_t vt[2], mk;
        auto fetch = [&](int u) {
            const int pair = cl + u * nclusters;
            const uint4* qp = reinterpret_cast<const uint4*>(q + ((size_t)pair * 16 + g) * kD) + tq;
            const uint4* kp = reinterpret_cast<const uint4*>(k_tree + ((size_t)pair * kT + g) * kD) + tq;
#pragma unroll
            for (int j = 0; j < 4; ++j) {
                qa[j] = __ldg(qp + 4 * j);
                qb[j] = __ldg(qp + 4 * j + 8 * kD / 8);
                kt[j] = __ldg(kp + 4 * j);
            }
            const unsigned short* vp =
                reinterpret_cast<const unsigned short*>(v_tree) + ((size_t)pair * kT + 2 * tq) * kD + 16 * mem + g;
#pragma unroll
            for (int n = 0; n < 2; ++n)
                vt[n] = (uint32_t)__ldg(vp + 8 * n) | ((uint32_t)__ldg(vp + 8 * n + kD) << 16);
            mk = __ldg(reinterpret_cast<const uint32_t*>(mask + (size_t)(pair / kHkv) * kT * kT + g * kT + 2 * tq));
        };
        fetch(0);
        for (int u = 0; u < npairs; ++u) {
            const int s = u & 1;
            const int pair = cl + u * nclusters;
            float acc[2][4], lt[4] = {0.f, 0.f, 0.f, 0.f}, mt0, mt1;
            {
                float st[4] = {0.f, 0.f, 0.f, 0.f};
#pragma unroll
                for (int j = 0; j < 4; ++j) {
                    mma16816(st, qa[j].x, qb[j].x, qa[j].y, qb[j].y, kt[j].x, kt[j].y);
                    mma16816(st, qa[j].z, qb[j].z, qa[j].w, qb[j].w, kt[j].z, kt[j].w);
                }
                const float bias0 = (1.0f - __uint_as_float(mk << 16)) * (-1.0e9f * 1.4426950408889634f);
                const float bias1 = (1.0f - __uint_as_float(mk & 0xffff0000u)) * (-1.0e9f * 1.4426950408889634f);
                const float t0 = fmaf(st[0], c, bias0), t1 = fmaf(st[1], c, bias1);
                const float t2 = fmaf(st[2], c, bias0), t3 = fmaf(st[3], c, bias1);
                mt0 = quad_max(fmaxf(t0, t1));
                mt1 = quad_max(fmaxf(t2, t3));
                const uint32_t a0 = pack_bf16(ex2(t0 - mt0), ex2(t1 - mt0));
                const uint32_t a1 = pack_bf16(ex2(t2 - mt1), ex2(t3 - mt1));
#pragma unroll
                for (int n = 0; n < 2; ++n) {
                    acc[n][0] = 0.f; acc[n][1] = 0.f; acc[n][2] = 0.f; acc[n][3] = 0.f;
                    mma16816(acc[n], a0, a1, 0u, 0u, vt[n], 0u);
                }
                mma16816(lt, a0, a1, 0u, 0u, kOnes, 0u);
            }
            if (u + 1 < npairs) fetch(u + 1);
            jitter(1);

            float w0[kG], w1[kG];
            mbar_wait_cluster(bar_ml + (u & 3) * 8, (u >> 2) & 1);
            {
                float4 ml[kG];
#pragma unroll
                for (int j = 0; j < kG; ++j)
                    ml[j] = *reinterpret_cast<const float4*>(sgen + kSmMl + (u & 3) * kMlBytes + j * 128 + g * 16);
                float M0 = mt0, M1 = mt1;
#pragma unroll
                for (int j = 0; j < kG; ++j) { M0 = fmaxf(M0, ml[j].x); M1 = fmaxf(M1, ml[j].z); }
                const float wt0 = ex2(mt0 - M0), wt1 = ex2(mt1 - M1);
                float L0 = lt[0] * wt0, L1 = lt[2] * wt1;
#pragma unroll
                for (int j = 0; j < kG; ++j) {
                    w0[j] = ex2(ml[j].x - M0);
                    w1[j] = ex2(ml[j].z - M1);
                    L0 = fmaf(ml[j].y, w0[j], L0);
                    L1 = fmaf(ml[j].w, w1[j], L1);
                }
                const float inv0 = 1.0f / L0, inv1 = 1.0f / L1;
#pragma unroll
                for (int j = 0; j < kG; ++j) { w0[j] *= inv0; w1[j] *= inv1; }
#pragma unroll
                for (int n = 0; n < 2; ++n) {
                    acc[n][0] *= wt0 * inv0; acc[n][1] *= wt0 * inv0;
                    acc[n][2] *= wt1 * inv1; acc[n][3] *= wt1 * inv1;
                }
            }
            __syncwarp();
            if (lane == 0) mbar_expect_tx(bar_ml + (u & 3) * 8, kMlBytes);
            jitter(2);

            mbar_wait_cluster(bar_rfull + s * 8, (u >> 1) & 1);
            const unsigned char* rb = sgen + kSmRecv + s * kRecvBytes;
#pragma unroll
            for (int j = 0; j < kG; ++j)
#pragma unroll
                for (int n = 0; n < 2; ++n) {
                    const float4 v = *reinterpret_cast<const float4*>(rb + ((j * 2 + n) * 32 + lane) * 16);
                    acc[n][0] = fmaf(v.x, w0[j], acc[n][0]); acc[n][1] = fmaf(v.y, w0[j], acc[n][1]);
                    acc[n][2] = fmaf(v.z, w1[j], acc[n][2]); acc[n][3] = fmaf(v.w, w1[j], acc[n][3]);
                }
            uint32_t* o0 = reinterpret_cast<uint32_t*>(out + ((size_t)pair * 16 + g) * kD + 16 * mem + 2 * tq);
#pragma unroll
            for (int n = 0; n < 2; ++n) {
                o0[4 * n] = pack_bf16(acc[n][0], acc[n][1]);
                o0[4 * n + 8 * kD / 2] = pack_bf16(acc[n][2], acc[n][3]);
            }
            jitter(6);
            __syncwarp();
            if (lane == 0) {
                mbar_expect_tx(bar_rfull + s * 8, kRecvBytes);
                mbar_arrive(bar_cdone + s * 8);
            }
        }
    } else {
        const int g = lane >> 2;
        const int tq = lane & 3;
        const int mi = lane >> 3;
        const int lr = lane & 7;

        const uint32_t k_row = (uint32_t)(16 * warp + 8 * (mi >> 1) + lr) * 128u;
        const uint32_t k_x = (uint32_t)(((mi & 1) ^ lr) << 4);
        const uint32_t q_row = (uint32_t)(8 * (mi & 1) + lr) * 128u;
        const uint32_t q_x = (uint32_t)(((mi >> 1) ^ lr) << 4);
        const uint32_t v_row = (uint32_t)(warp >> 1) * 8192u + (uint32_t)(8 * (mi & 1) + lr) * 128u;
        const uint32_t v_x0 = (uint32_t)(((4 * (warp & 1) + (mi >> 1)) ^ lr) << 4);
        const uint32_t v_x1 = v_x0 ^ 32u;

        uint4* const pbuf = reinterpret_cast<uint4*>(sgen + kSmP);
        float* const smax = reinterpret_cast<float*>(sgen + kSmMax);
        float* const ssum = reinterpret_cast<float*>(sgen + kSmSum);

        const uint32_t rem0 = mapa(sb, 2 * warp), rem1 = mapa(sb, 2 * warp + 1);
        const uint32_t rem_ml = (tq == 0 ? rem0 : rem1);

        int slot = 0;
        uint32_t phase = 0;

        auto release = [&](int sl) {
            __syncwarp();
            if (lane == 0) mbar_arrive(bar_empty + sl * 8);
        };
        auto load_k = [&](uint32_t (&f)[8][4], int sl) {
            const uint32_t base = sb + kSmRing + sl * kTileBytes + k_row;
#pragma unroll
            for (int ks = 0; ks < 8; ++ks)
                ldsm4(f[ks][0], f[ks][1], f[ks][2], f[ks][3], base + (ks >> 2) * 8192 + (k_x ^ ((ks & 3) << 5)));
        };
        auto load_v = [&](uint32_t (&f)[8][4], int sl) {
            const uint32_t base = sb + kSmRing + sl * kTileBytes + v_row;
#pragma unroll
            for (int ks = 0; ks < 4; ++ks) {
                ldsm4t(f[2 * ks][0], f[2 * ks][1], f[2 * ks][2], f[2 * ks][3], base + ks * 2048 + v_x0);
                ldsm4t(f[2 * ks + 1][0], f[2 * ks + 1][1], f[2 * ks + 1][2], f[2 * ks + 1][3], base + ks * 2048 + v_x1);
            }
        };

        for (int u = 0; u < npairs; ++u) {
            mbar_wait(bar_q, u & 1);
            uint32_t qf[8][4];
            {
                const uint32_t qa = sb + kSmQ + q_row;
#pragma unroll
                for (int ks = 0; ks < 8; ++ks)
                    ldsm4(qf[ks][0], qf[ks][1], qf[ks][2], qf[ks][3], qa + (ks >> 2) * 2048 + (q_x ^ ((ks & 3) << 5)));
            }
            float s[kRun][2][4];
            auto qk = [&](const uint32_t (&f)[8][4], float (&d)[2][4]) {
                float h[2][4];
#pragma unroll
                for (int e = 0; e < 4; ++e) { d[0][e] = 0.f; d[1][e] = 0.f; h[0][e] = 0.f; h[1][e] = 0.f; }
#pragma unroll
                for (int ks = 0; ks < 8; ks += 2) {
                    mma16816(d[0], qf[ks][0], qf[ks][1], qf[ks][2], qf[ks][3], f[ks][0], f[ks][1]);
                    mma16816(d[1], qf[ks][0], qf[ks][1], qf[ks][2], qf[ks][3], f[ks][2], f[ks][3]);
                    mma16816(h[0], qf[ks + 1][0], qf[ks + 1][1], qf[ks + 1][2], qf[ks + 1][3], f[ks + 1][0], f[ks + 1][1]);
                    mma16816(h[1], qf[ks + 1][0], qf[ks + 1][1], qf[ks + 1][2], qf[ks + 1][3], f[ks + 1][2], f[ks + 1][3]);
                }
#pragma unroll
                for (int e = 0; e < 4; ++e) { d[0][e] += h[0][e]; d[1][e] += h[1][e]; }
            };
#pragma unroll
            for (int t = 0; t < kRun; ++t) {
                uint32_t f[8][4];
                mbar_wait(bar_full + slot * 8, phase);
                load_k(f, slot);
                release(slot);
                qk(f, s[t]);
                if (++slot == kNS) { slot = 0; phase ^= 1; }
            }
            jitter(3);
            float x0 = fmaxf(s[0][0][0], s[0][0][1]), x1 = fmaxf(s[0][0][2], s[0][0][3]);
#pragma unroll
            for (int t = 0; t < kRun; ++t)
#pragma unroll
                for (int n = 0; n < 2; ++n) {
                    x0 = fmaxf(x0, fmaxf(s[t][n][0], s[t][n][1]));
                    x1 = fmaxf(x1, fmaxf(s[t][n][2], s[t][n][3]));
                }
            x0 = quad_max(x0);
            x1 = quad_max(x1);
            if (tq == 0) {
                smax[g * kCW + warp] = x0;
                smax[(g + 8) * kCW + warp] = x1;
            }
            asm volatile("bar.sync 1, %0;" ::"n"(kCW * 32) : "memory");
            {
                const float4 a = *reinterpret_cast<const float4*>(smax + g * kCW);
                const float4 b = *reinterpret_cast<const float4*>(smax + (g + 8) * kCW);
                x0 = fmaxf(fmaxf(a.x, a.y), fmaxf(a.z, a.w));
                x1 = fmaxf(fmaxf(b.x, b.y), fmaxf(b.z, b.w));
            }
            const float m0 = x0 * c, m1 = x1 * c;
            float r0 = 0.f, r1 = 0.f;
#pragma unroll
            for (int t = 0; t < kRun; ++t) {
                uint32_t pf[4];
#pragma unroll
                for (int n = 0; n < 2; ++n) {
                    const float p0 = ex2(fmaf(s[t][n][0], c, -m0)), p1 = ex2(fmaf(s[t][n][1], c, -m0));
                    const float p2 = ex2(fmaf(s[t][n][2], c, -m1)), p3 = ex2(fmaf(s[t][n][3], c, -m1));
                    r0 += p0 + p1;
                    r1 += p2 + p3;
                    pf[2 * n] = pack_bf16(p0, p1);
                    pf[2 * n + 1] = pack_bf16(p2, p3);
                }
                pbuf[(t * kCW + warp) * 32 + lane] = make_uint4(pf[0], pf[1], pf[2], pf[3]);
            }
            r0 = quad_sum(r0);
            r1 = quad_sum(r1);
            if (tq == 0) {
                ssum[g * kCW + warp] = r0;
                ssum[(g + 8) * kCW + warp] = r1;
            }
            asm volatile("bar.sync 1, %0;" ::"n"(kCW * 32) : "memory");
            jitter(4);
            {
                const float4 a = *reinterpret_cast<const float4*>(ssum + g * kCW);
                const float4 b = *reinterpret_cast<const float4*>(ssum + (g + 8) * kCW);
                if (u == 0) asm volatile("barrier.cluster.wait.acquire.aligned;" ::: "memory");
                if (tq < 2)
                    st_async4(rem_ml + kSmMl + (u & 3) * kMlBytes + mem * 128 + g * 16, m0, (a.x + a.y) + (a.z + a.w), m1,
                              (b.x + b.y) + (b.z + b.w), rem_ml + kSmBar + (2 * kNS + 6 + (u & 3)) * 8);
            }
            float o[2][4][4];
#pragma unroll
            for (int n = 0; n < 8; ++n) { o[n >> 2][n & 3][0] = 0.f; o[n >> 2][n & 3][1] = 0.f; o[n >> 2][n & 3][2] = 0.f; o[n >> 2][n & 3][3] = 0.f; }
            auto pv = [&](const uint32_t (&f)[8][4], const uint4* pa) {
#pragma unroll
                for (int ks = 0; ks < 4; ++ks) {
                    const uint4 a = pa[ks];
                    mma16816(o[ks & 1][0], a.x, a.y, a.z, a.w, f[2 * ks][0], f[2 * ks][1]);
                    mma16816(o[ks & 1][1], a.x, a.y, a.z, a.w, f[2 * ks][2], f[2 * ks][3]);
                    mma16816(o[ks & 1][2], a.x, a.y, a.z, a.w, f[2 * ks + 1][0], f[2 * ks + 1][1]);
                    mma16816(o[ks & 1][3], a.x, a.y, a.z, a.w, f[2 * ks + 1][2], f[2 * ks + 1][3]);
                }
            };
#pragma unroll
            for (int t = 0; t < kRun; ++t) {
                uint32_t f[8][4];
                uint4 pa[kCW];
#pragma unroll
                for (int i = 0; i < kCW; ++i) pa[i] = pbuf[(t * kCW + i) * 32 + lane];
                if (t == kRun - 1 && u > 0) mbar_wait(bar_cdone + ((u - 1) & 1) * 8, ((u - 1) >> 1) & 1);
                mbar_wait(bar_full + slot * 8, phase);
                load_v(f, slot);
                release(slot);
                pv(f, pa);
                if (++slot == kNS) { slot = 0; phase ^= 1; }
            }
            jitter(5);
            {
                const uint32_t doff = kSmRecv + (u & 1) * kRecvBytes + (uint32_t)(mem * 64 + lane) * 16u;
                const uint32_t boff = kSmBar + (2 * kNS + 2 + (u & 1)) * 8;
#pragma unroll
                for (int n = 0; n < 4; ++n) {
                    const uint32_t rem = n < 2 ? rem0 : rem1;
                    st_async4(rem + doff + (n & 1) * 512, o[0][n][0] + o[1][n][0], o[0][n][1] + o[1][n][1],
                              o[0][n][2] + o[1][n][2], o[0][n][3] + o[1][n][3], rem + boff);
                }
            }
        }
    }
}

typedef CUresult (*EncodeTiledFn)(CUtensorMap*, CUtensorMapDataType, cuuint32_t, void*, const cuuint64_t*,
                                  const cuuint64_t*, const cuuint32_t*, const cuuint32_t*, CUtensorMapInterleave,
                                  CUtensorMapSwizzle, CUtensorMapL2promotion, CUtensorMapFloatOOBfill);

void make_map(EncodeTiledFn enc, CUtensorMap* tm, const void* base, int rows, int box_rows) {
    cuuint64_t dims[3] = {64, (cuuint64_t)rows, 2};
    cuuint64_t strides[2] = {256, 128};
    cuuint32_t box[3] = {64, (cuuint32_t)box_rows, 2};
    cuuint32_t es[3] = {1, 1, 1};
    enc(tm, CU_TENSOR_MAP_DATA_TYPE_BFLOAT16, 3, const_cast<void*>(base), dims, strides, box, es,
        CU_TENSOR_MAP_INTERLEAVE_NONE, CU_TENSOR_MAP_SWIZZLE_128B, CU_TENSOR_MAP_L2_PROMOTION_L2_256B,
        CU_TENSOR_MAP_FLOAT_OOB_FILL_NONE);
}

}

extern "C" void kernel_launch(void* const* d_in, const int* in_sizes, int n_in, void* d_out, int out_size) {
    (void)in_sizes; (void)n_in; (void)out_size;
    const __nv_bfloat16* q = (const __nv_bfloat16*)d_in[0];
    const void* k_cache = d_in[1];
    const void* v_cache = d_in[2];
    const __nv_bfloat16* k_tree = (const __nv_bfloat16*)d_in[3];
    const __nv_bfloat16* v_tree = (const __nv_bfloat16*)d_in[4];
    const __nv_bfloat16* mask = (const __nv_bfloat16*)d_in[5];

    static EncodeTiledFn enc = nullptr;
    static int nclusters = 0;
    static void* progress = nullptr;
    if (!enc) {
        void* fn = nullptr;
        cudaDriverEntryPointQueryResult qr;
        cudaGetDriverEntryPoint("cuTensorMapEncodeTiled", &fn, cudaEnableDefault, &qr);
        enc = (EncodeTiledFn)fn;
        cudaGetSymbolAddress(&progress, g_progress);
        cudaFuncSetAttribute(tree_attn_kernel, cudaFuncAttributeMaxDynamicSharedMemorySize, kSmemBytes);
        cudaFuncSetAttribute(tree_attn_kernel, cudaFuncAttributePreferredSharedMemoryCarveout,
                             cudaSharedmemCarveoutMaxShared);
        cudaLaunchConfig_t cfg = {};
        cfg.gridDim = dim3(kG * CFG_NC);
        cfg.blockDim = dim3(kThreads);
        cfg.dynamicSmemBytes = kSmemBytes;
        cudaLaunchAttribute at;
        at.id = cudaLaunchAttributeClusterDimension;
        at.val.clusterDim.x = kG; at.val.clusterDim.y = 1; at.val.clusterDim.z = 1;
        cfg.attrs = &at;
        cfg.numAttrs = 1;
        if (cudaOccupancyMaxActiveClusters(&nclusters, tree_attn_kernel, &cfg) != cudaSuccess || nclusters < 1) {
            (void)cudaGetLastError();
            nclusters = 8;
        }
        if (nclusters > CFG_NC) nclusters = CFG_NC;
        if (nclusters > 1) nclusters &= ~1;
    }
    CUtensorMap tmK, tmV, tmQ;
    make_map(enc, &tmK, k_cache, kPairs * kC, kTileKeys);
    make_map(enc, &tmV, v_cache, kPairs * kC, kTileKeys);
    make_map(enc, &tmQ, q, kPairs * 16, 16);
    tree_attn_kernel<<<kG * nclusters, kThreads, kSmemBytes>>>(tmK, tmV, tmQ, q, k_tree, v_tree, mask,
                                                              (__nv_bfloat16*)d_out, (const __nv_bfloat16*)k_cache,
                                                              (unsigned*)progress, kPairs / nclusters,
                                                              kPairs % nclusters);
}
```
